```python
import torch

def _softmax(x, axis=-1):
    return torch.softmax(x, dim=axis)
def _gelu(x):
    return torch.nn.functional.gelu(x, approximate="tanh")
def _silu(x):
    return torch.nn.functional.silu(x)
def _sigmoid(x):
    return torch.sigmoid(x)
def _layernorm(x, axis=-1, eps=1e-5):
    m = x.mean(dim=axis, keepdim=True)
    v = x.var(dim=axis, keepdim=True, unbiased=False)
    return (x - m) / torch.sqrt(v + eps)
def _scatter_add(tgt, idx, src, axis=0):
    return tgt.clone().index_add_(axis, idx, src)
def _segment_sum(src, seg, n):
    out = torch.zeros((n,) + src.shape[1:], dtype=src.dtype)
    return out.index_add_(0, seg, src)
def _pad(x, pw):
    flat = tuple(v for pair in reversed(pw) for v in pair)
    return torch.nn.functional.pad(x, flat)

kernel_name = 'parallel_sum__ssm_conv_s4d__geglu_ffn__prompt'

def setup_inputs():

    _w = (lambda a: (lambda t: t.to(torch.bfloat16) if t.is_floating_point() else t)(torch.as_tensor(a)))
    def _A_setup():
        Bsz, L, D, N = 1, 2048, 576, 128
        return {
            "u": _w((lambda *s: torch.randn(*s, dtype=torch.bfloat16) * 0.05)(Bsz, L, D)),
            "log_A_real": _w((lambda *s: torch.randn(*s, dtype=torch.bfloat16) * 3.2)(D, N) * 0.5),
            "A_imag": _w((lambda *s: torch.randn(*s, dtype=torch.bfloat16) * 0.2)(D, N) * 3.14),
            "C_real": _w((lambda *s: torch.randn(*s, dtype=torch.bfloat16) * 3.2)(D, N) / N ** 0.5),
            "C_imag": _w((lambda *s: torch.randn(*s, dtype=torch.bfloat16) * 3.2)(D, N) / N ** 0.5),
            "log_dt": _w((lambda *s: torch.randn(*s, dtype=torch.bfloat16) * 0.2)(D) * 0.5 - 4.0),
            "D_skip": _w((lambda *s: torch.randn(*s, dtype=torch.bfloat16) * 0.4)(D)),
        }
    _A_in = _A_setup()

    def _B_setup():
        B, S, D, F = 1, 2048, 576, 4608
        return {
            "x": _w((lambda *s: torch.randn(*s, dtype=torch.bfloat16) * 0.05)(B, S, D)),
            "w_gate": _w((lambda *s: torch.randn(*s, dtype=torch.bfloat16) * 0.05)(D, F)),
            "w_up": _w((lambda *s: torch.randn(*s, dtype=torch.bfloat16) * 0.05)(D, F)),
            "w_down": _w((lambda *s: torch.randn(*s, dtype=torch.bfloat16) * 0.05)(F, D)),
        }
    _B_in = _B_setup()

    return {
        "A_u": _A_in["u"],
        "A_log_A_real": _A_in["log_A_real"],
        "A_A_imag": _A_in["A_imag"],
        "A_C_real": _A_in["C_real"],
        "A_C_imag": _A_in["C_imag"],
        "A_log_dt": _A_in["log_dt"],
        "A_D_skip": _A_in["D_skip"],
        "B_x": _B_in["x"],
        "B_w_gate": _B_in["w_gate"],
        "B_w_up": _B_in["w_up"],
        "B_w_down": _B_in["w_down"],
    }

def reference(A_u, A_log_A_real, A_A_imag, A_C_real, A_C_imag, A_log_dt, A_D_skip, B_x, B_w_gate, B_w_up, B_w_down):
    def _A_ref(u, log_A_real, A_imag, C_real, C_imag, log_dt, D_skip):
        L = u.shape[1]
        dt = torch.exp(log_dt)
        A = -torch.exp(log_A_real) + 1j * A_imag
        C = (C_real + 1j * C_imag) * dt[:, None]
        pos = (lambda x, dt: x.to(dt))(torch.arange(L), log_dt.dtype)
        P = torch.exp((A * dt[:, None])[:, :, None] * pos[None, None, :])
        K = 2.0 * torch.einsum("dn,dnl->dl", C, P).real
        L2 = 2 * L
        u_t = (lambda x, *d: x.permute(*d))(u, 0, 2, 1)
        Kf = (lambda x, *a, **k: torch.fft.rfft(x.float(), *a, **k))(K, L2)
        Uf = (lambda x, *a, **k: torch.fft.rfft(x.float(), *a, **k))(u_t, L2)
        y = (lambda x, *a, **k: torch.fft.irfft(x, *a, **k).to(torch.bfloat16))(Uf * Kf[None, :, :], L2)[:, :, :L]
        y = (lambda x, *d: x.permute(*d))(y, 0, 2, 1)
        return y + u * D_skip[None, None, :]

    def _B_ref(x, w_gate, w_up, w_down):
        return (_gelu(x @ w_gate) * (x @ w_up)) @ w_down

    x = A_u
    xn = _layernorm(x, axis=-1)
    return x + _A_ref(xn, A_log_A_real, A_A_imag, A_C_real, A_C_imag, A_log_dt, A_D_skip) + _B_ref(xn, B_w_gate, B_w_up, B_w_down)
```

```cpp
#include <cuda_runtime.h>
#include <cuda_bf16.h>
#include <cuda.h>
#include <stdint.h>

namespace {

constexpr int kL = 2048, kD = 576, kF = 4608, kN = 128;
constexpr int kCtas = 132, kFfn = 128;
constexpr int kStages = 4;
#define KNOBS kPace = 100, kLate = 100, kRetry = 100, kHNum = 5, kUNum = 4
constexpr int KNOBS;
constexpr uint32_t kTagMask = 0x00010001u;
constexpr uint32_t kBlk = 16384;
constexpr uint32_t OFF_RING = 9 * kBlk;
constexpr uint32_t OFF_SSM = OFF_RING + kStages * kBlk;
constexpr uint32_t OFF_BAR = OFF_SSM + 19200;
constexpr uint32_t SMEM_TOTAL = OFF_BAR + 256;
constexpr uint32_t B_FULL = 0, B_EMPTY = 4, B_AFULL = 8, B_HREADY = 17, B_X7FREE = 24, B_UBAR = 25, B_PAR = 29, B_PROG = 30;
constexpr uint32_t S_Q = 0, S_U = 5120, S_UPITCH = 2304, S_RT = 9728, S_RTBYTES = 1536, S_P = 11264, S_V = 11776, S_Y = 0, S_YPITCH = 4224, S_YF = 16896;

__device__ uint4 g_ut[kD * 256];
__device__ uint4 g_yt[kD * kL / 8];
__device__ uint4 g_h[kFfn * 9 * 1024];
__device__ uint4 g_rt[kD * 96];
__device__ unsigned g_misc[2 * 32];
__device__ unsigned g_hint[16 * 32];
__device__ unsigned g_launch[kCtas * 32];
__device__ const uint32_t g_qidx[5 * 128] = {
0x01505415, 0x01505415, 0x01505415, 0x01505415, 0x01505415, 0x01505415, 0x01505415, 0x01505415, 0x00100015, 0x00300801, 0x00501003, 0x00701805, 0x01906007, 0x01b06819, 0x01d0701b, 0x01f0781d,
0x0310c01f, 0x0330c831, 0x0350d033, 0x0370d835, 0x04912037, 0x04b12849, 0x04d1304b, 0x04f1384d, 0x0611804f, 0x06318861, 0x06519063, 0x06719865, 0x0791e067, 0x07b1e879, 0x07d1f07b, 0x07f1f87d,
0x0912407f, 0x09324891, 0x09525093, 0x09725895, 0x0a92a097, 0x0ab2a8a9, 0x0ad2b0ab, 0x0af2b8ad, 0x0c1300af, 0x0c3308c1, 0x0c5310c3, 0x0c7318c5, 0x0d9360c7, 0x0db368d9, 0x0dd370db, 0x0df378dd,
0x0f13c0df, 0x0f33c8f1, 0x0f53d0f3, 0x0f73d8f5, 0x109420f7, 0x10b42909, 0x10d4310b, 0x10f4390d, 0x1214810f, 0x12348921, 0x12549123, 0x12749925, 0x1394e127, 0x13b4e939, 0x13d4f13b, 0x13f4f93d,
0x1515413f, 0x15354951, 0x15555153, 0x15755955, 0x1695a157, 0x16b5a969, 0x16d5b16b, 0x16f5b96d, 0x1816016f, 0x18360981, 0x18561183, 0x18761985, 0x19966187, 0x19b66999, 0x19d6719b, 0x19f6799d,
0x1b16c19f, 0x1b36c9b1, 0x1b56d1b3, 0x1b76d9b5, 0x1c9721b7, 0x1cb729c9, 0x1cd731cb, 0x1cf739cd, 0x1e1781cf, 0x1e3789e1, 0x1e5791e3, 0x1e7799e5, 0x1f97e1e7, 0x1fb7e9f9, 0x1fd7f1fb, 0x1ff7f9fd,
0x211841ff, 0x21384a11, 0x21585213, 0x21785a15, 0x2298a217, 0x22b8aa29, 0x22d8b22b, 0x22f8ba2d, 0x2419022f, 0x24390a41, 0x24591243, 0x24791a45, 0x25996247, 0x25b96a59, 0x25d9725b, 0x25f97a5d,
0x2719c25f, 0x2739ca71, 0x2759d273, 0x2779da75, 0x289a2277, 0x28ba2a89, 0x28da328b, 0x28fa3a8d, 0x2a1a828f, 0x2a3a8aa1, 0x2a5a92a3, 0x2a7a9aa5, 0x2b9ae2a7, 0x2bbaeab9, 0x2bdaf2bb, 0x2bfafabd,
0x2d1b42bf, 0x2d3b4ad1, 0x2d5b52d3, 0x2d7b5ad5, 0x2e9ba2d7, 0x2ebbaae9, 0x2edbb2eb, 0x2efbbaed, 0x008022ef, 0x00a02408, 0x00a0280a, 0x02002c0a, 0x02008020, 0x02208420, 0x02208822, 0x03808c22,
0x0380e038, 0x03a0e438, 0x03a0e83a, 0x0500ec3a, 0x05014050, 0x05214450, 0x05214852, 0x06814c52, 0x0681a068, 0x06a1a468, 0x06a1a86a, 0x0801ac6a, 0x08020080, 0x08220480, 0x08220882, 0x09820c82,
0x09826098, 0x09a26498, 0x09a2689a, 0x0b026c9a, 0x0b02c0b0, 0x0b22c4b0, 0x0b22c8b2, 0x0c82ccb2, 0x0c8320c8, 0x0ca324c8, 0x0ca328ca, 0x0e032cca, 0x0e0380e0, 0x0e2384e0, 0x0e2388e2, 0x0f838ce2,
0x0f83e0f8, 0x0fa3e4f8, 0x0fa3e8fa, 0x1103ecfa, 0x11044110, 0x11244510, 0x11244912, 0x12844d12, 0x1284a128, 0x12a4a528, 0x12a4a92a, 0x1404ad2a, 0x14050140, 0x14250540, 0x14250942, 0x15850d42,
0x15856158, 0x15a56558, 0x15a5695a, 0x17056d5a, 0x1705c170, 0x1725c570, 0x1725c972, 0x1885cd72, 0x18862188, 0x18a62588, 0x18a6298a, 0x1a062d8a, 0x1a0681a0, 0x1a2685a0, 0x1a2689a2, 0x1b868da2,
0x1b86e1b8, 0x1ba6e5b8, 0x1ba6e9ba, 0x1d06edba, 0x1d0741d0, 0x1d2745d0, 0x1d2749d2, 0x1e874dd2, 0x1e87a1e8, 0x1ea7a5e8, 0x1ea7a9ea, 0x2007adea, 0x20080200, 0x20280600, 0x20280a02, 0x21880e02,
0x21886218, 0x21a86618, 0x21a86a1a, 0x23086e1a, 0x2308c230, 0x2328c630, 0x2328ca32, 0x2488ce32, 0x24892248, 0x24a92648, 0x24a92a4a, 0x26092e4a, 0x26098260, 0x26298660, 0x26298a62, 0x27898e62,
0x2789e278, 0x27a9e678, 0x27a9ea7a, 0x2909ee7a, 0x290a4290, 0x292a4690, 0x292a4a92, 0x2a8a4e92, 0x2a8aa2a8, 0x2aaaa6a8, 0x2aaaaaaa, 0x2c0aaeaa, 0x2c0b02c0, 0x2c2b06c0, 0x2c2b0ac2, 0x2d8b0ec2,
0x2d8b62d8, 0x2dab66d8, 0x2dab6ada, 0x2f0b6eda, 0x2f0bc2f0, 0x2f2bc6f0, 0x2f2bcaf2, 0x00cbcef2, 0x00c0300c, 0x00d0300c, 0x00d0340d, 0x0240900d, 0x02409024, 0x02509024, 0x02509425, 0x03c0f025,
0x03c0f03c, 0x03d0f03c, 0x03d0f43d, 0x0541503d, 0x05415054, 0x05515054, 0x05515455, 0x06c1b055, 0x06c1b06c, 0x06d1b06c, 0x06d1b46d, 0x0842106d, 0x08421084, 0x08521084, 0x08521485, 0x09c27085,
0x09c2709c, 0x09d2709c, 0x09d2749d, 0x0b42d09d, 0x0b42d0b4, 0x0b52d0b4, 0x0b52d4b5, 0x0cc330b5, 0x0cc330cc, 0x0cd330cc, 0x0cd334cd, 0x0e4390cd, 0x0e4390e4, 0x0e5390e4, 0x0e5394e5, 0x0fc3f0e5,
0x0fc3f0fc, 0x0fd3f0fc, 0x0fd3f4fd, 0x114450fd, 0x11445114, 0x11545114, 0x11545515, 0x12c4b115, 0x12c4b12c, 0x12d4b12c, 0x12d4b52d, 0x1445112d, 0x14451144, 0x14551144, 0x14551545, 0x15c57145,
0x15c5715c, 0x15d5715c, 0x15d5755d, 0x1745d15d, 0x1745d174, 0x1755d174, 0x1755d575, 0x18c63175, 0x18c6318c, 0x18d6318c, 0x18d6358d, 0x1a46918d, 0x1a4691a4, 0x1a5691a4, 0x1a5695a5, 0x1bc6f1a5,
0x1bc6f1bc, 0x1bd6f1bc, 0x1bd6f5bd, 0x1d4751bd, 0x1d4751d4, 0x1d5751d4, 0x1d5755d5, 0x1ec7b1d5, 0x1ec7b1ec, 0x1ed7b1ec, 0x1ed7b5ed, 0x204811ed, 0x20481204, 0x20581204, 0x20581605, 0x21c87205,
0x21c8721c, 0x21d8721c, 0x21d8761d, 0x2348d21d, 0x2348d234, 0x2358d234, 0x2358d635, 0x24c93235, 0x24c9324c, 0x24d9324c, 0x24d9364d, 0x2649924d, 0x26499264, 0x26599264, 0x26599665, 0x27c9f265,
0x27c9f27c, 0x27d9f27c, 0x27d9f67d, 0x294a527d, 0x294a5294, 0x295a5294, 0x295a5695, 0x2acab295, 0x2acab2ac, 0x2adab2ac, 0x2adab6ad, 0x2c4b12ad, 0x2c4b12c4, 0x2c5b12c4, 0x2c5b16c5, 0x2dcb72c5,
0x2dcb72dc, 0x2ddb72dc, 0x2ddb76dd, 0x2f4bd2dd, 0x2f4bd2f4, 0x2f5bd2f4, 0x2f5bd6f5, 0x00e03af5, 0x00e0380e, 0x00f0380e, 0x00f03c0f, 0x0260980f, 0x02609826, 0x02709826, 0x02709c27, 0x03e0f827,
0x03e0f83e, 0x03f0f83e, 0x03f0fc3f, 0x0561583f, 0x05615856, 0x05715856, 0x05715c57, 0x06e1b857, 0x06e1b86e, 0x06f1b86e, 0x06f1bc6f, 0x0862186f, 0x08621886, 0x08721886, 0x08721c87, 0x09e27887,
0x09e2789e, 0x09f2789e, 0x09f27c9f, 0x0b62d89f, 0x0b62d8b6, 0x0b72d8b6, 0x0b72dcb7, 0x0ce338b7, 0x0ce338ce, 0x0cf338ce, 0x0cf33ccf, 0x0e6398cf, 0x0e6398e6, 0x0e7398e6, 0x0e739ce7, 0x0fe3f8e7,
0x0fe3f8fe, 0x0ff3f8fe, 0x0ff3fcff, 0x116458ff, 0x11645916, 0x11745916, 0x11745d17, 0x12e4b917, 0x12e4b92e, 0x12f4b92e, 0x12f4bd2f, 0x1465192f, 0x14651946, 0x14751946, 0x14751d47, 0x15e57947,
0x15e5795e, 0x15f5795e, 0x15f57d5f, 0x1765d95f, 0x1765d976, 0x1775d976, 0x1775dd77, 0x18e63977, 0x18e6398e, 0x18f6398e, 0x18f63d8f, 0x1a66998f, 0x1a6699a6, 0x1a7699a6, 0x1a769da7, 0x1be6f9a7,
0x1be6f9be, 0x1bf6f9be, 0x1bf6fdbf, 0x1d6759bf, 0x1d6759d6, 0x1d7759d6, 0x1d775dd7, 0x1ee7b9d7, 0x1ee7b9ee, 0x1ef7b9ee, 0x1ef7bdef, 0x206819ef, 0x20681a06, 0x20781a06, 0x20781e07, 0x21e87a07,
0x21e87a1e, 0x21f87a1e, 0x21f87e1f, 0x2368da1f, 0x2368da36, 0x2378da36, 0x2378de37, 0x24e93a37, 0x24e93a4e, 0x24f93a4e, 0x24f93e4f, 0x26699a4f, 0x26699a66, 0x26799a66, 0x26799e67, 0x27e9fa67,
0x27e9fa7e, 0x27f9fa7e, 0x27f9fe7f, 0x296a5a7f, 0x296a5a96, 0x297a5a96, 0x297a5e97, 0x2aeaba97, 0x2aeabaae, 0x2afabaae, 0x2afabeaf, 0x2c6b1aaf, 0x2c6b1ac6, 0x2c7b1ac6, 0x2c7b1ec7, 0x2deb7ac7,
0x2deb7ade, 0x2dfb7ade, 0x2dfb7edf, 0x2f6bdadf, 0x2f6bdaf6, 0x2f7bdaf6, 0x2f7bdef7, 0x010042f7, 0x01004010, 0x01004010, 0x01504010, 0x01505415, 0x01505415, 0x01505415, 0x01505415, 0x01505415,
0x01505415, 0x01505415, 0x01505415, 0x01505415, 0x01505415, 0x01505415, 0x01505415, 0x01505415, 0x01505415, 0x01505415, 0x01505415, 0x01505415, 0x01505415, 0x01505415, 0x01505415, 0x01505415,
0x01505415, 0x01505415, 0x01505415, 0x01505415, 0x01505415, 0x01505415, 0x01505415, 0x01505415, 0x01505415, 0x01505415, 0x01505415, 0x01505415, 0x01505415, 0x01505415, 0x01505415, 0x01505415,
0x01505415, 0x01505415, 0x01505415, 0x01505415, 0x01505415, 0x01505415, 0x01505415, 0x01505415, 0x01505415, 0x01505415, 0x01505415, 0x01505415, 0x01505415, 0x01505415, 0x01505415, 0x01505415,
0x01505415, 0x01505415, 0x01505415, 0x01505415, 0x01505415, 0x01505415, 0x01505415, 0x01505415, 0x01505415, 0x01505415, 0x01505415, 0x01505415, 0x01505415, 0x01505415, 0x01505415, 0x01505415,
0x01505415, 0x01505415, 0x01505415, 0x01505415, 0x01505415, 0x01505415, 0x01505415, 0x01505415, 0x01505415, 0x01505415, 0x01505415, 0x01505415, 0x01505415, 0x01505415, 0x01505415, 0x01505415,
0x01505415, 0x01505415, 0x01505415, 0x01505415, 0x01505415, 0x01505415, 0x01505415, 0x01505415, 0x01505415, 0x01505415, 0x01505415, 0x01505415, 0x01505415, 0x01505415, 0x01505415, 0x01505415,
0x01505415, 0x01505415, 0x01505415, 0x01505415, 0x01505415, 0x01505415, 0x01505415, 0x01505415, 0x01505415, 0x01505415, 0x01505415, 0x01505415, 0x01505415, 0x01505415, 0x01505415, 0x01505415
};

struct Params {
  const __nv_bfloat16 *u, *logA, *Aim, *Cre, *Cim, *logdt, *Dskip, *wdown;
  __nv_bfloat16* out;
};

__device__ __forceinline__ uint32_t smem_u32(const void* p) { return (uint32_t)__cvta_generic_to_shared(p); }
__device__ __forceinline__ void mbar_init(uint32_t bar, uint32_t cnt) { asm volatile("mbarrier.init.shared::cta.b64 [%0], %1;" :: "r"(bar), "r"(cnt) : "memory"); }
__device__ __forceinline__ void mbar_expect_tx(uint32_t bar, uint32_t bytes) { asm volatile("mbarrier.arrive.expect_tx.shared::cta.b64 _, [%0], %1;" :: "r"(bar), "r"(bytes) : "memory"); }
__device__ __forceinline__ void mbar_arrive(uint32_t bar) { asm volatile("mbarrier.arrive.shared::cta.b64 _, [%0];" :: "r"(bar) : "memory"); }
__device__ __forceinline__ void mbar_arrive_if(uint32_t bar, bool pred) {
  asm volatile("{\n.reg .pred p;\nsetp.ne.u32 p, %1, 0;\n@p mbarrier.arrive.shared::cta.b64 _, [%0];\n}" :: "r"(bar), "r"((uint32_t)pred) : "memory");
}
__device__ __forceinline__ void sts_if(uint32_t a, uint32_t v, bool pred) {
  asm volatile("{\n.reg .pred p;\nsetp.ne.u32 p, %2, 0;\n@p st.volatile.shared.u32 [%0], %1;\n}" :: "r"(a), "r"(v), "r"((uint32_t)pred) : "memory");
}
__device__ __forceinline__ void prog_wait(uint32_t a, uint32_t target) {
  asm volatile("{\n.reg .pred p;\n.reg .u32 n, v;\nmov.u32 n, 0;\nLAB_WAIT:\nld.volatile.shared.u32 v, [%0];\nsetp.ge.u32 p, v, %1;\n@p bra LAB_DONE;\n"
               "nanosleep.u32 32;\nadd.u32 n, n, 1;\nsetp.lt.u32 p, n, 100000;\n@p bra LAB_WAIT;\nLAB_DONE:\n}" :: "r"(a), "r"(target) : "memory");
}
__device__ __forceinline__ void mbar_arrive_remote_if(uint32_t rbar, bool pred) {
  asm volatile("{\n.reg .pred p;\nsetp.ne.u32 p, %1, 0;\n@p mbarrier.arrive.shared::cluster.b64 _, [%0];\n}" :: "r"(rbar), "r"((uint32_t)pred) : "memory");
}
__device__ __forceinline__ uint32_t mapa(uint32_t a, uint32_t cta) { uint32_t r; asm volatile("mapa.shared::cluster.u32 %0, %1, %2;" : "=r"(r) : "r"(a), "r"(cta)); return r; }
__device__ __forceinline__ void mbar_wait(uint32_t bar, uint32_t parity) {
  asm volatile("{\n.reg .pred p;\n.reg .u32 n;\nmbarrier.try_wait.parity.shared::cta.b64 p, [%0], %1;\n@p bra LAB_DONE;\nmov.u32 n, 0;\nLAB_WAIT:\n"
               "mbarrier.try_wait.parity.shared::cta.b64 p, [%0], %1;\n@p bra LAB_DONE;\n"
               "add.u32 n, n, 1;\nsetp.lt.u32 p, n, 3000;\n@p bra LAB_WAIT;\nLAB_DONE:\n}" :: "r"(bar), "r"(parity) : "memory");
}
__device__ __forceinline__ void flag_wait(const unsigned* f, unsigned target) {
  asm volatile("{\n.reg .pred p;\n.reg .u32 n, v;\n.reg .s32 df;\nmov.u32 n, 0;\nLAB_WAIT:\nld.relaxed.gpu.global.u32 v, [%0];\nsub.s32 df, v, %1;\nsetp.ge.s32 p, df, 0;\n@p bra LAB_DONE;\n"
               "nanosleep.u32 100;\nadd.u32 n, n, 1;\nsetp.lt.u32 p, n, 20000;\n@p bra LAB_WAIT;\nLAB_DONE:\nld.acquire.gpu.global.u32 v, [%0];\n}" :: "l"(f), "r"(target) : "memory");
}
__device__ __forceinline__ void flag_add(unsigned* f) { asm volatile("red.release.gpu.global.add.u32 [%0], 1;" :: "l"(f) : "memory"); }
__device__ __forceinline__ void lds128(uint32_t a, uint4& v) {
  asm volatile("ld.shared.v4.u32 {%0,%1,%2,%3}, [%4];" : "=r"(v.x), "=r"(v.y), "=r"(v.z), "=r"(v.w) : "r"(a) : "memory");
}
__device__ __forceinline__ void st_part(uint4* p, uint4 v) {
  asm volatile("st.global.v4.u32 [%0], {%1,%2,%3,%4};" :: "l"(p), "r"(v.x), "r"(v.y), "r"(v.z), "r"(v.w) : "memory");
}
__device__ __forceinline__ unsigned read_epoch() { unsigned v; asm volatile("ld.relaxed.gpu.global.u32 %0, [%1];" : "=r"(v) : "l"(&g_launch[blockIdx.x * 32]) : "memory"); return v + 1; }
__device__ __forceinline__ void fence_async_all() { asm volatile("fence.proxy.async;" ::: "memory"); }
__device__ __forceinline__ void fence_async_smem() { asm volatile("fence.proxy.async.shared::cta;" ::: "memory"); }
__device__ __forceinline__ void cluster_arrive() { asm volatile("barrier.cluster.arrive.relaxed.aligned;" ::: "memory"); }
__device__ __forceinline__ void cluster_wait() { asm volatile("barrier.cluster.wait.aligned;" ::: "memory"); }
__device__ __forceinline__ void bulk_g2s(uint32_t dst, const void* src, uint32_t bytes, uint32_t bar) {
  asm volatile("cp.async.bulk.shared::cluster.global.mbarrier::complete_tx::bytes [%0], [%1], %2, [%3];" :: "r"(dst), "l"(src), "r"(bytes), "r"(bar) : "memory");
}
__device__ __forceinline__ void tma2d(uint32_t dst, const CUtensorMap* tm, int c0, int c1, uint32_t bar) {
  asm volatile("cp.async.bulk.tensor.2d.shared::cluster.global.mbarrier::complete_tx::bytes [%0], [%1, {%3, %4}], [%2];" :: "r"(dst), "l"(tm), "r"(bar), "r"(c0), "r"(c1) : "memory");
}
__device__ __forceinline__ void ldsm4(uint32_t a, uint32_t& r0, uint32_t& r1, uint32_t& r2, uint32_t& r3) {
  asm volatile("ldmatrix.sync.aligned.m8n8.x4.shared.b16 {%0,%1,%2,%3}, [%4];" : "=r"(r0), "=r"(r1), "=r"(r2), "=r"(r3) : "r"(a) : "memory");
}
__device__ __forceinline__ void ldsm4t(uint32_t a, uint32_t& r0, uint32_t& r1, uint32_t& r2, uint32_t& r3) {
  asm volatile("ldmatrix.sync.aligned.m8n8.x4.trans.shared.b16 {%0,%1,%2,%3}, [%4];" : "=r"(r0), "=r"(r1), "=r"(r2), "=r"(r3) : "r"(a) : "memory");
}
__device__ __forceinline__ void stsm4(uint32_t a, uint32_t r0, uint32_t r1, uint32_t r2, uint32_t r3) {
  asm volatile("stmatrix.sync.aligned.m8n8.x4.shared.b16 [%0], {%1,%2,%3,%4};" :: "r"(a), "r"(r0), "r"(r1), "r"(r2), "r"(r3) : "memory");
}
__device__ __forceinline__ void stsm4t(uint32_t a, uint32_t r0, uint32_t r1, uint32_t r2, uint32_t r3) {
  asm volatile("stmatrix.sync.aligned.m8n8.x4.trans.shared.b16 [%0], {%1,%2,%3,%4};" :: "r"(a), "r"(r0), "r"(r1), "r"(r2), "r"(r3) : "memory");
}
__device__ __forceinline__ void tma2d_mc(uint32_t dst, const CUtensorMap* tm, int c0, int c1, uint32_t bar) {
  asm volatile("cp.async.bulk.tensor.2d.shared::cluster.global.mbarrier::complete_tx::bytes.multicast::cluster [%0], [%1, {%3, %4}], [%2], %5;"
               :: "r"(dst), "l"(tm), "r"(bar), "r"(c0), "r"(c1), "h"((uint16_t)3) : "memory");
}
__device__ __forceinline__ void tma5d_mc(uint32_t dst, const CUtensorMap* tm, int c0, int c4, uint32_t bar) {
  asm volatile("cp.async.bulk.tensor.5d.shared::cluster.global.mbarrier::complete_tx::bytes.multicast::cluster [%0], [%1, {%3, %5, %5, %5, %4}], [%2], %6;"
               :: "r"(dst), "l"(tm), "r"(bar), "r"(c0), "r"(c4), "r"(0), "h"((uint16_t)3) : "memory");
}
__device__ __forceinline__ void tma2d_pf(const CUtensorMap* tm, int c0, int c1) {
  asm volatile("cp.async.bulk.prefetch.tensor.2d.L2.global [%0, {%1, %2}];" :: "l"(tm), "r"(c0), "r"(c1) : "memory");
}
__device__ __forceinline__ void tma5d_pf(const CUtensorMap* tm, int c0, int c4) {
  asm volatile("cp.async.bulk.prefetch.tensor.5d.L2.global [%0, {%1, %3, %3, %3, %2}];" :: "l"(tm), "r"(c0), "r"(c4), "r"(0) : "memory");
}
__device__ __forceinline__ void bulk_pf(const void* src, uint32_t bytes) {
  asm volatile("cp.async.bulk.prefetch.L2.global [%0], %1;" :: "l"(src), "r"(bytes) : "memory");
}
__device__ __forceinline__ void tmap_pf(const CUtensorMap* tm) { asm volatile("prefetch.tensormap [%0];" :: "l"(tm) : "memory"); }
__device__ __forceinline__ void wg_fence() { asm volatile("wgmma.fence.sync.aligned;" ::: "memory"); }
__device__ __forceinline__ void wg_commit() { asm volatile("wgmma.commit_group.sync.aligned;" ::: "memory"); }
template<int N> __device__ __forceinline__ void wg_wait() { asm volatile("wgmma.wait_group.sync.aligned %0;" :: "n"(N) : "memory"); }
template<int R> __device__ __forceinline__ void reg_inc() { asm volatile("setmaxnreg.inc.sync.aligned.u32 %0;" :: "n"(R)); }
template<int R> __device__ __forceinline__ void reg_dec() { asm volatile("setmaxnreg.dec.sync.aligned.u32 %0;" :: "n"(R)); }
__device__ __forceinline__ void bar_sync(int id, int n) { asm volatile("bar.sync %0, %1;" :: "r"(id), "r"(n) : "memory"); }
__device__ __forceinline__ void bar_arrive(int id, int n) { asm volatile("bar.arrive %0, %1;" :: "r"(id), "r"(n) : "memory"); }
__device__ __forceinline__ uint64_t make_desc(uint32_t addr, uint32_t lbo, uint32_t sbo, uint32_t swz) {
  return (uint64_t)((addr & 0x3FFFF) >> 4) | ((uint64_t)((lbo & 0x3FFFF) >> 4) << 16) | ((uint64_t)((sbo & 0x3FFFF) >> 4) << 32) | ((uint64_t)swz << 62);
}
__device__ __forceinline__ uint64_t desc2(uint32_t lo, uint32_t hi) { uint64_t d; asm("mov.b64 %0, {%1, %2};" : "=l"(d) : "r"(lo), "r"(hi)); return d; }
__device__ __forceinline__ uint64_t desc_sw128(uint32_t lo) { return desc2(lo, 0x40000040u); }
template<int NR> __device__ __forceinline__ void pin(float (&d)[NR]) {
#pragma unroll
  for (int i = 0; i < NR; i++) asm volatile("" : "+f"(d[i]) :: "memory");
}
__device__ __forceinline__ uint32_t pack_bf16(float lo, float hi) { uint32_t r; asm("cvt.rn.bf16x2.f32 %0, %1, %2;" : "=r"(r) : "f"(hi), "f"(lo)); return r; }
__device__ __forceinline__ float bf_lo(uint32_t w) { return __uint_as_float(w << 16); }
__device__ __forceinline__ float bf_hi(uint32_t w) { return __uint_as_float(w & 0xffff0000u); }
__device__ __forceinline__ float bf_round(float x) { return bf_lo(pack_bf16(x, 0.f)); }
__device__ __forceinline__ uint32_t bf2_fma(uint32_t a, uint32_t b, uint32_t c) { uint32_t r; asm("fma.rn.bf16x2 %0, %1, %2, %3;" : "=r"(r) : "r"(a), "r"(b), "r"(c)); return r; }
__device__ __forceinline__ void hmma(float (&d)[4], uint32_t a0, uint32_t a1, uint32_t a2, uint32_t a3, uint32_t b0, uint32_t b1) {
  asm("mma.sync.aligned.m16n8k16.row.col.f32.bf16.bf16.f32 {%0,%1,%2,%3}, {%4,%5,%6,%7}, {%8,%9}, {%0,%1,%2,%3};"
      : "+f"(d[0]), "+f"(d[1]), "+f"(d[2]), "+f"(d[3]) : "r"(a0), "r"(a1), "r"(a2), "r"(a3), "r"(b0), "r"(b1));
}
__device__ __forceinline__ int fresh_tid() { int v; asm volatile("mov.u32 %0, %%tid.x;" : "=r"(v)); return v; }
__device__ __forceinline__ int fresh_cta() { int v; asm volatile("mov.u32 %0, %%ctaid.x;" : "=r"(v)); return v; }
__device__ __forceinline__ uint32_t fresh_smem(const void* base) {
  uint32_t v; asm volatile("{\n.reg .u64 t;\ncvta.to.shared.u64 t, %1;\ncvt.u32.u64 %0, t;\n}" : "=r"(v) : "l"(base)); return __shfl_sync(0xffffffffu, v, 0);
}
#define ROLE_LOCALS \
  const uint32_t sm = fresh_smem(smem_raw), bars = sm + OFF_BAR; \
  const int tid = fresh_tid(), lane = tid & 31, warp = __shfl_sync(0xffffffffu, tid >> 5, 0), wg = warp >> 2; \
  const int b = fresh_cta(), mi = b & 15, fj = b >> 4; \
  (void)bars; (void)lane; (void)wg; (void)mi; (void)fj;
template<typename T> __device__ __forceinline__ T& at(uint8_t* base, uint32_t off) { return *reinterpret_cast<T*>(base + off); }

__device__ __forceinline__ void wg_ss_n128(float (&d)[64], uint64_t da, uint64_t db, int scale_d) {
  asm volatile("{\n.reg .pred p;\nsetp.ne.b32 p, %66, 0;\n"
    "wgmma.mma_async.sync.aligned.m64n128k16.f32.bf16.bf16 {%0, %1, %2, %3, %4, %5, %6, %7, %8, %9, %10, %11, %12, %13, %14, %15, %16, %17, %18, %19, %20, %21, %22, %23, %24, %25, %26, %27, %28, %29, %30, %31, %32, %33, %34, %35, %36, %37, %38, %39, %40, %41, %42, %43, %44, %45, %46, %47, %48, %49, %50, %51, %52, %53, %54, %55, %56, %57, %58, %59, %60, %61, %62, %63}, %64, %65, p, 1, 1, 0, 1;\n}\n"
    : "+f"(d[0]), "+f"(d[1]), "+f"(d[2]), "+f"(d[3]), "+f"(d[4]), "+f"(d[5]), "+f"(d[6]), "+f"(d[7]), "+f"(d[8]), "+f"(d[9]), "+f"(d[10]), "+f"(d[11]), "+f"(d[12]), "+f"(d[13]), "+f"(d[14]), "+f"(d[15]), "+f"(d[16]), "+f"(d[17]), "+f"(d[18]), "+f"(d[19]), "+f"(d[20]), "+f"(d[21]), "+f"(d[22]), "+f"(d[23]), "+f"(d[24]), "+f"(d[25]), "+f"(d[26]), "+f"(d[27]), "+f"(d[28]), "+f"(d[29]), "+f"(d[30]), "+f"(d[31]), "+f"(d[32]), "+f"(d[33]), "+f"(d[34]), "+f"(d[35]), "+f"(d[36]), "+f"(d[37]), "+f"(d[38]), "+f"(d[39]), "+f"(d[40]), "+f"(d[41]), "+f"(d[42]), "+f"(d[43]), "+f"(d[44]), "+f"(d[45]), "+f"(d[46]), "+f"(d[47]), "+f"(d[48]), "+f"(d[49]), "+f"(d[50]), "+f"(d[51]), "+f"(d[52]), "+f"(d[53]), "+f"(d[54]), "+f"(d[55]), "+f"(d[56]), "+f"(d[57]), "+f"(d[58]), "+f"(d[59]), "+f"(d[60]), "+f"(d[61]), "+f"(d[62]), "+f"(d[63])
    : "l"(da), "l"(db), "r"(scale_d));
}
__device__ __forceinline__ void wg_ss_n64(float (&d)[64], uint64_t da, uint64_t db, int scale_d) {
  asm volatile("{\n.reg .pred p;\nsetp.ne.b32 p, %34, 0;\n"
    "wgmma.mma_async.sync.aligned.m64n64k16.f32.bf16.bf16 {%0, %1, %2, %3, %4, %5, %6, %7, %8, %9, %10, %11, %12, %13, %14, %15, %16, %17, %18, %19, %20, %21, %22, %23, %24, %25, %26, %27, %28, %29, %30, %31}, %32, %33, p, 1, 1, 0, 1;\n}\n"
    : "+f"(d[0]), "+f"(d[1]), "+f"(d[2]), "+f"(d[3]), "+f"(d[4]), "+f"(d[5]), "+f"(d[6]), "+f"(d[7]), "+f"(d[8]), "+f"(d[9]), "+f"(d[10]), "+f"(d[11]), "+f"(d[12]), "+f"(d[13]), "+f"(d[14]), "+f"(d[15]), "+f"(d[16]), "+f"(d[17]), "+f"(d[18]), "+f"(d[19]), "+f"(d[20]), "+f"(d[21]), "+f"(d[22]), "+f"(d[23]), "+f"(d[24]), "+f"(d[25]), "+f"(d[26]), "+f"(d[27]), "+f"(d[28]), "+f"(d[29]), "+f"(d[30]), "+f"(d[31])
    : "l"(da), "l"(db), "r"(scale_d));
}
__device__ __forceinline__ void wg_ss_n24(float (&d)[12], uint64_t da, uint64_t db, int scale_d) {
  asm volatile("{\n.reg .pred p;\nsetp.ne.b32 p, %14, 0;\n"
    "wgmma.mma_async.sync.aligned.m64n24k16.f32.bf16.bf16 {%0, %1, %2, %3, %4, %5, %6, %7, %8, %9, %10, %11}, %12, %13, p, 1, 1, 0, 0;\n}\n"
    : "+f"(d[0]), "+f"(d[1]), "+f"(d[2]), "+f"(d[3]), "+f"(d[4]), "+f"(d[5]), "+f"(d[6]), "+f"(d[7]), "+f"(d[8]), "+f"(d[9]), "+f"(d[10]), "+f"(d[11])
    : "l"(da), "l"(db), "r"(scale_d));
}
template<int N> __device__ __forceinline__ void wg_rs(float (&d)[N / 2], uint32_t a0, uint32_t a1, uint32_t a2, uint32_t a3, uint64_t db, int scale_d);
template<> __device__ __forceinline__ void wg_rs<128>(float (&d)[64], uint32_t a0, uint32_t a1, uint32_t a2, uint32_t a3, uint64_t db, int scale_d) {
  asm volatile("{\n.reg .pred p;\nsetp.ne.b32 p, %69, 0;\n"
    "wgmma.mma_async.sync.aligned.m64n128k16.f32.bf16.bf16 {%0, %1, %2, %3, %4, %5, %6, %7, %8, %9, %10, %11, %12, %13, %14, %15, %16, %17, %18, %19, %20, %21, %22, %23, %24, %25, %26, %27, %28, %29, %30, %31, %32, %33, %34, %35, %36, %37, %38, %39, %40, %41, %42, %43, %44, %45, %46, %47, %48, %49, %50, %51, %52, %53, %54, %55, %56, %57, %58, %59, %60, %61, %62, %63}, {%64, %65, %66, %67}, %68, p, 1, 1, 0;\n}\n"
    : "+f"(d[0]), "+f"(d[1]), "+f"(d[2]), "+f"(d[3]), "+f"(d[4]), "+f"(d[5]), "+f"(d[6]), "+f"(d[7]), "+f"(d[8]), "+f"(d[9]), "+f"(d[10]), "+f"(d[11]), "+f"(d[12]), "+f"(d[13]), "+f"(d[14]), "+f"(d[15]), "+f"(d[16]), "+f"(d[17]), "+f"(d[18]), "+f"(d[19]), "+f"(d[20]), "+f"(d[21]), "+f"(d[22]), "+f"(d[23]), "+f"(d[24]), "+f"(d[25]), "+f"(d[26]), "+f"(d[27]), "+f"(d[28]), "+f"(d[29]), "+f"(d[30]), "+f"(d[31]), "+f"(d[32]), "+f"(d[33]), "+f"(d[34]), "+f"(d[35]), "+f"(d[36]), "+f"(d[37]), "+f"(d[38]), "+f"(d[39]), "+f"(d[40]), "+f"(d[41]), "+f"(d[42]), "+f"(d[43]), "+f"(d[44]), "+f"(d[45]), "+f"(d[46]), "+f"(d[47]), "+f"(d[48]), "+f"(d[49]), "+f"(d[50]), "+f"(d[51]), "+f"(d[52]), "+f"(d[53]), "+f"(d[54]), "+f"(d[55]), "+f"(d[56]), "+f"(d[57]), "+f"(d[58]), "+f"(d[59]), "+f"(d[60]), "+f"(d[61]), "+f"(d[62]), "+f"(d[63])
    : "r"(a0), "r"(a1), "r"(a2), "r"(a3), "l"(db), "r"(scale_d));
}
template<> __device__ __forceinline__ void wg_rs<112>(float (&d)[56], uint32_t a0, uint32_t a1, uint32_t a2, uint32_t a3, uint64_t db, int scale_d) {
  asm volatile("{\n.reg .pred p;\nsetp.ne.b32 p, %61, 0;\n"
    "wgmma.mma_async.sync.aligned.m64n112k16.f32.bf16.bf16 {%0, %1, %2, %3, %4, %5, %6, %7, %8, %9, %10, %11, %12, %13, %14, %15, %16, %17, %18, %19, %20, %21, %22, %23, %24, %25, %26, %27, %28, %29, %30, %31, %32, %33, %34, %35, %36, %37, %38, %39, %40, %41, %42, %43, %44, %45, %46, %47, %48, %49, %50, %51, %52, %53, %54, %55}, {%56, %57, %58, %59}, %60, p, 1, 1, 0;\n}\n"
    : "+f"(d[0]), "+f"(d[1]), "+f"(d[2]), "+f"(d[3]), "+f"(d[4]), "+f"(d[5]), "+f"(d[6]), "+f"(d[7]), "+f"(d[8]), "+f"(d[9]), "+f"(d[10]), "+f"(d[11]), "+f"(d[12]), "+f"(d[13]), "+f"(d[14]), "+f"(d[15]), "+f"(d[16]), "+f"(d[17]), "+f"(d[18]), "+f"(d[19]), "+f"(d[20]), "+f"(d[21]), "+f"(d[22]), "+f"(d[23]), "+f"(d[24]), "+f"(d[25]), "+f"(d[26]), "+f"(d[27]), "+f"(d[28]), "+f"(d[29]), "+f"(d[30]), "+f"(d[31]), "+f"(d[32]), "+f"(d[33]), "+f"(d[34]), "+f"(d[35]), "+f"(d[36]), "+f"(d[37]), "+f"(d[38]), "+f"(d[39]), "+f"(d[40]), "+f"(d[41]), "+f"(d[42]), "+f"(d[43]), "+f"(d[44]), "+f"(d[45]), "+f"(d[46]), "+f"(d[47]), "+f"(d[48]), "+f"(d[49]), "+f"(d[50]), "+f"(d[51]), "+f"(d[52]), "+f"(d[53]), "+f"(d[54]), "+f"(d[55])
    : "r"(a0), "r"(a1), "r"(a2), "r"(a3), "l"(db), "r"(scale_d));
}
template<> __device__ __forceinline__ void wg_rs<96>(float (&d)[48], uint32_t a0, uint32_t a1, uint32_t a2, uint32_t a3, uint64_t db, int scale_d) {
  asm volatile("{\n.reg .pred p;\nsetp.ne.b32 p, %53, 0;\n"
    "wgmma.mma_async.sync.aligned.m64n96k16.f32.bf16.bf16 {%0, %1, %2, %3, %4, %5, %6, %7, %8, %9, %10, %11, %12, %13, %14, %15, %16, %17, %18, %19, %20, %21, %22, %23, %24, %25, %26, %27, %28, %29, %30, %31, %32, %33, %34, %35, %36, %37, %38, %39, %40, %41, %42, %43, %44, %45, %46, %47}, {%48, %49, %50, %51}, %52, p, 1, 1, 0;\n}\n"
    : "+f"(d[0]), "+f"(d[1]), "+f"(d[2]), "+f"(d[3]), "+f"(d[4]), "+f"(d[5]), "+f"(d[6]), "+f"(d[7]), "+f"(d[8]), "+f"(d[9]), "+f"(d[10]), "+f"(d[11]), "+f"(d[12]), "+f"(d[13]), "+f"(d[14]), "+f"(d[15]), "+f"(d[16]), "+f"(d[17]), "+f"(d[18]), "+f"(d[19]), "+f"(d[20]), "+f"(d[21]), "+f"(d[22]), "+f"(d[23]), "+f"(d[24]), "+f"(d[25]), "+f"(d[26]), "+f"(d[27]), "+f"(d[28]), "+f"(d[29]), "+f"(d[30]), "+f"(d[31]), "+f"(d[32]), "+f"(d[33]), "+f"(d[34]), "+f"(d[35]), "+f"(d[36]), "+f"(d[37]), "+f"(d[38]), "+f"(d[39]), "+f"(d[40]), "+f"(d[41]), "+f"(d[42]), "+f"(d[43]), "+f"(d[44]), "+f"(d[45]), "+f"(d[46]), "+f"(d[47])
    : "r"(a0), "r"(a1), "r"(a2), "r"(a3), "l"(db), "r"(scale_d));
}
template<> __device__ __forceinline__ void wg_rs<80>(float (&d)[40], uint32_t a0, uint32_t a1, uint32_t a2, uint32_t a3, uint64_t db, int scale_d) {
  asm volatile("{\n.reg .pred p;\nsetp.ne.b32 p, %45, 0;\n"
    "wgmma.mma_async.sync.aligned.m64n80k16.f32.bf16.bf16 {%0, %1, %2, %3, %4, %5, %6, %7, %8, %9, %10, %11, %12, %13, %14, %15, %16, %17, %18, %19, %20, %21, %22, %23, %24, %25, %26, %27, %28, %29, %30, %31, %32, %33, %34, %35, %36, %37, %38, %39}, {%40, %41, %42, %43}, %44, p, 1, 1, 0;\n}\n"
    : "+f"(d[0]), "+f"(d[1]), "+f"(d[2]), "+f"(d[3]), "+f"(d[4]), "+f"(d[5]), "+f"(d[6]), "+f"(d[7]), "+f"(d[8]), "+f"(d[9]), "+f"(d[10]), "+f"(d[11]), "+f"(d[12]), "+f"(d[13]), "+f"(d[14]), "+f"(d[15]), "+f"(d[16]), "+f"(d[17]), "+f"(d[18]), "+f"(d[19]), "+f"(d[20]), "+f"(d[21]), "+f"(d[22]), "+f"(d[23]), "+f"(d[24]), "+f"(d[25]), "+f"(d[26]), "+f"(d[27]), "+f"(d[28]), "+f"(d[29]), "+f"(d[30]), "+f"(d[31]), "+f"(d[32]), "+f"(d[33]), "+f"(d[34]), "+f"(d[35]), "+f"(d[36]), "+f"(d[37]), "+f"(d[38]), "+f"(d[39])
    : "r"(a0), "r"(a1), "r"(a2), "r"(a3), "l"(db), "r"(scale_d));
}
template<> __device__ __forceinline__ void wg_rs<64>(float (&d)[32], uint32_t a0, uint32_t a1, uint32_t a2, uint32_t a3, uint64_t db, int scale_d) {
  asm volatile("{\n.reg .pred p;\nsetp.ne.b32 p, %37, 0;\n"
    "wgmma.mma_async.sync.aligned.m64n64k16.f32.bf16.bf16 {%0, %1, %2, %3, %4, %5, %6, %7, %8, %9, %10, %11, %12, %13, %14, %15, %16, %17, %18, %19, %20, %21, %22, %23, %24, %25, %26, %27, %28, %29, %30, %31}, {%32, %33, %34, %35}, %36, p, 1, 1, 0;\n}\n"
    : "+f"(d[0]), "+f"(d[1]), "+f"(d[2]), "+f"(d[3]), "+f"(d[4]), "+f"(d[5]), "+f"(d[6]), "+f"(d[7]), "+f"(d[8]), "+f"(d[9]), "+f"(d[10]), "+f"(d[11]), "+f"(d[12]), "+f"(d[13]), "+f"(d[14]), "+f"(d[15]), "+f"(d[16]), "+f"(d[17]), "+f"(d[18]), "+f"(d[19]), "+f"(d[20]), "+f"(d[21]), "+f"(d[22]), "+f"(d[23]), "+f"(d[24]), "+f"(d[25]), "+f"(d[26]), "+f"(d[27]), "+f"(d[28]), "+f"(d[29]), "+f"(d[30]), "+f"(d[31])
    : "r"(a0), "r"(a1), "r"(a2), "r"(a3), "l"(db), "r"(scale_d));
}
template<> __device__ __forceinline__ void wg_rs<16>(float (&d)[8], uint32_t a0, uint32_t a1, uint32_t a2, uint32_t a3, uint64_t db, int scale_d) {
  asm volatile("{\n.reg .pred p;\nsetp.ne.b32 p, %13, 0;\n"
    "wgmma.mma_async.sync.aligned.m64n16k16.f32.bf16.bf16 {%0, %1, %2, %3, %4, %5, %6, %7}, {%8, %9, %10, %11}, %12, p, 1, 1, 0;\n}\n"
    : "+f"(d[0]), "+f"(d[1]), "+f"(d[2]), "+f"(d[3]), "+f"(d[4]), "+f"(d[5]), "+f"(d[6]), "+f"(d[7])
    : "r"(a0), "r"(a1), "r"(a2), "r"(a3), "l"(db), "r"(scale_d));
}

__device__ __forceinline__ uint32_t gelu_mul2(float g0, float g1, float u0, float u1) {
  uint32_t gh, s2, t2;
  float t0, t1;
  asm("cvt.rn.f16x2.f32 %0, %1, %2;" : "=r"(gh) : "f"(g1), "f"(g0));
  asm("mul.rn.f16x2 %0, %1, %1;" : "=r"(s2) : "r"(gh));
  asm("fma.rn.f16x2 %0, %1, %2, %3;" : "=r"(s2) : "r"(s2), "r"(0x28912891u), "r"(0x3a623a62u));
  asm("mul.rn.f16x2 %0, %1, %2;" : "=r"(s2) : "r"(s2), "r"(gh));
  asm("tanh.approx.f16x2 %0, %1;" : "=r"(t2) : "r"(s2));
  asm("{\n.reg .f16 l, h;\nmov.b32 {l, h}, %2;\ncvt.f32.f16 %0, l;\ncvt.f32.f16 %1, h;\n}" : "=f"(t0), "=f"(t1) : "r"(t2));
  const float q0 = g0 * u0, q1 = g1 * u1;
  return pack_bf16(fmaf(q0, t0, q0), fmaf(q1, t1, q1));
}
__device__ __forceinline__ void cexp_at(float a2, float b, float p, float& zr, float& zi) {
  float m; asm("ex2.approx.ftz.f32 %0, %1;" : "=f"(m) : "f"(a2 * p));
  float th = b * p;
  float k = rintf(th * 0.15915494309189535f);
  float r = fmaf(-k, 6.2831854820251465f, th);
  r = fmaf(-k, -1.7484556000744883e-7f, r);
  zr = m * __cosf(r);
  zi = m * __sinf(r);
}

template<int S> __device__ __forceinline__ void conv_group(float (&acc)[64 - 8 * S], uint32_t (&fin)[32], float (&far)[8], const uint32_t* qp,
                                                           const uint32_t* pp, uint32_t ub, uint32_t vb) {
  constexpr int NK = S < 4 ? 4 : 1;
  constexpr bool FAR = S == 2 || S == 3;
  uint32_t q[4 * NK], f[16];
#pragma unroll
  for (int k = 0; k < NK; k++) {
    q[4 * k] = qp[S * 256 + k * 64];
    q[4 * k + 1] = qp[S * 256 + k * 64 + 8];
    q[4 * k + 2] = qp[S * 256 + k * 64 - 8];
    asm volatile("mov.b32 %0, %1;" : "=r"(q[4 * k + 3]) : "r"(q[4 * k]));
    if (FAR) {
      const int o = -8 * (4 * (S - 2) + k);
      f[4 * k] = pp[o]; f[4 * k + 1] = pp[o + 8]; f[4 * k + 2] = pp[o - 4]; f[4 * k + 3] = pp[o + 4];
    }
  }
  pin(acc);
  if (FAR) pin(far);
  wg_fence();
#pragma unroll
  for (int k = 0; k < NK; k++) {
    wg_rs<128 - 16 * S>(acc, q[4 * k], q[4 * k + 1], q[4 * k + 2], q[4 * k + 3], make_desc(ub + (16 - 4 * k) * 16, S_UPITCH, 128, 0), (S > 0 || k > 0) ? 1 : 0);
    if (FAR) wg_rs<16>(far, f[4 * k], f[4 * k + 1], f[4 * k + 2], f[4 * k + 3], make_desc(vb + (4 * (S - 2) + k) * 576, 288, 144, 0), (S > 2 || k > 0) ? 1 : 0);
  }
  wg_commit();
  wg_wait<0>();
  pin(acc);
  if (FAR) pin(far);
#pragma unroll
  for (int i = 0; i < (S < 4 ? 4 : 16); i++) fin[4 * S + i] = pack_bf16(acc[2 * i], acc[2 * i + 1]);
  if constexpr (S < 4) {
    float nxt[56 - 8 * S];
#pragma unroll
    for (int i = 0; i < 56 - 8 * S; i++) asm volatile("mov.b32 %0, %1;" : "=f"(nxt[i]) : "f"(acc[8 + i]));
    conv_group<S + 1>(nxt, fin, far, qp, pp, ub, vb);
  }
}

#define CMUL(orr, oi, ar, ai, br, bi) do { const float r_ = (ar) * (br) - (ai) * (bi), i_ = (ar) * (bi) + (ai) * (br); (orr) = r_; (oi) = i_; } while (0)
struct ModePar { uint16_t la[2], ai[2], cr[2], ci[2], ldt, dsk; };
__device__ __forceinline__ ModePar kgen_load(const Params& p, int d) {
  const int n = d * kN + (threadIdx.x & 63);
  ModePar m;
#pragma unroll
  for (int c = 0; c < 2; c++) {
    m.la[c] = __ldg(reinterpret_cast<const uint16_t*>(p.logA) + n + 64 * c); m.ai[c] = __ldg(reinterpret_cast<const uint16_t*>(p.Aim) + n + 64 * c);
    m.cr[c] = __ldg(reinterpret_cast<const uint16_t*>(p.Cre) + n + 64 * c); m.ci[c] = __ldg(reinterpret_cast<const uint16_t*>(p.Cim) + n + 64 * c);
  }
  m.ldt = __ldg(reinterpret_cast<const uint16_t*>(p.logdt) + d); m.dsk = __ldg(reinterpret_cast<const uint16_t*>(p.Dskip) + d);
  return m;
}
__device__ __forceinline__ void kgen(const ModePar& m, uint8_t* s16, int d, int barid) {
  const int tid = threadIdx.x & 127, w = tid >> 5, lane = tid & 31, g = lane >> 2, t4 = lane & 3;
  const uint32_t sb = smem_u32(s16);
  const float dt = bf_round(expf(bf_lo(m.ldt)));
  float racc[12];
#pragma unroll 1
  for (int c = 0; c < 2; c++) {
    const float a2 = -bf_round(expf(bf_lo(c ? m.la[1] : m.la[0]))) * dt * 1.4426950408889634f, b = bf_lo(c ? m.ai[1] : m.ai[0]) * dt;
    float zr, zi;
    cexp_at(a2, b, w < 2 ? 8.f : 256.f, zr, zi);
    if (w < 2) {
      uint8_t* ka = s16 + w * 4096 + t4 * 4;
      float er = 1.f, ei = 0.f, fr = zr, fi = zi, sr, si;
      CMUL(sr, si, zr, zi, zr, zi);
#pragma unroll 1
      for (int i = 0; i < 4; i++, ka += 1024) {
#pragma unroll
        for (int k = 0; k < 4; k++) {
          at<uint32_t>(ka, (2 * k) * 128 + ((g ^ (2 * k)) << 4)) = pack_bf16(er, ei);
          at<uint32_t>(ka, (2 * k + 1) * 128 + ((g ^ (2 * k + 1)) << 4)) = pack_bf16(fr, fi);
          CMUL(er, ei, er, ei, sr, si); CMUL(fr, fi, fr, fi, sr, si);
        }
      }
    } else {
      uint8_t* kb = s16 + 8192 + (w & 1) * 3072 + t4 * 4;
#define PUTG(h, r, i) at<uint32_t>(kb, (h) * 128 + ((g ^ ((h) & 7)) << 4)) = pack_bf16((r), -(i))
      float z1r, z1i, z2r, z2i, yr, yi;
      cexp_at(a2, b, 1.f, z1r, z1i);
      CMUL(z2r, z2i, zr, zi, zr, zi);
      float gr = 2.f * (bf_lo(c ? m.cr[1] : m.cr[0]) * dt), gi = 2.f * (bf_lo(c ? m.ci[1] : m.ci[0]) * dt);
      CMUL(yr, yi, gr, gi, z2r, z2i);
      CMUL(yr, yi, yr, yi, z2r, z2i);
#pragma unroll 1
      for (int k = 16; k < 21; k++) { PUTG(k, yr, yi); CMUL(yr, yi, yr, yi, zr, zi); }
      at<uint32_t>(kb, 21 * 128 + ((g ^ 5) << 4)) = 0u;
#pragma unroll 1
      for (int k = 0; k < 2; k++) {
        PUTG(4 * k, gr, gi);
        CMUL(yr, yi, gr, gi, zr, zi); PUTG(8 + 2 * k, yr, yi);
        CMUL(yr, yi, yr, yi, zr, zi); PUTG(12 + k, yr, yi);
        CMUL(yr, yi, yr, yi, zr, zi); PUTG(14 + k, yr, yi);
        CMUL(gr, gi, gr, gi, z1r, z1i); PUTG(4 * k + 1, gr, gi);
        CMUL(gr, gi, gr, gi, z1r, z1i); PUTG(4 * k + 2, gr, gi);
        CMUL(yr, yi, gr, gi, zr, zi); PUTG(9 + 2 * k, yr, yi);
        CMUL(gr, gi, gr, gi, z1r, z1i); PUTG(4 * k + 3, gr, gi);
        CMUL(gr, gi, gr, gi, z1r, z1i);
      }
#undef PUTG
    }
    fence_async_smem();
    bar_sync(barid, 128);
    pin(racc);
    wg_fence();
    const uint32_t alo = ((sb & 0x3FFFF) >> 4) | (1u << 16);
#pragma unroll
    for (int k = 0; k < 8; k++)
      wg_ss_n24(racc, desc_sw128(alo + (k >> 2) * 256 + (k & 3) * 2), desc_sw128(alo + 512 + (k >> 2) * 192 + (k & 3) * 2), (c > 0 || k > 0) ? 1 : 0);
    wg_commit();
    wg_wait<0>();
    pin(racc);
    bar_sync(barid, 128);
  }
  if (tid == 0) racc[0] += bf_lo(m.dsk);
  if (w < 2) {
    uint32_t* ro = reinterpret_cast<uint32_t*>(g_rt + d * 96) + (16 * w + g) * 12 + t4;
#pragma unroll
    for (int j = 0; j < 3; j++) {
      ro[4 * j] = pack_bf16(racc[4 * j], racc[4 * j + 1]);
      ro[96 + 4 * j] = pack_bf16(racc[4 * j + 2], racc[4 * j + 3]);
    }
  }
}
__device__ __forceinline__ void acc_bf2(float& lo, float& hi, uint32_t w) { lo += bf_lo(w); hi += bf_hi(w); }

__device__ __forceinline__ void ssm_role(uint8_t* sp, uint32_t ubar, int d0, int barid, unsigned epoch) {
  const int tid = fresh_tid() & 127, w = tid >> 5, lane = tid & 31, g = lane >> 2, t4 = lane & 3;
  const uint32_t sb = smem_u32(sp);
#pragma unroll 1
  for (int ch = 0; ch < 4; ch++) {
    const int d = d0 + ch;
    if (tid == 0) {
      if (ch == 0) { flag_wait(&g_misc[0], kFfn * epoch); fence_async_all(); }
      mbar_expect_tx(ubar, 4096 + S_RTBYTES);
      bulk_g2s(sb + S_RT, g_rt + d * 96, S_RTBYTES, ubar);
      bulk_g2s(sb + S_U + 256, g_ut + d * 256, 2048, ubar);
      bulk_g2s(sb + S_U + S_UPITCH + 256, g_ut + d * 256 + 128, 2048, ubar);
    }
    uint32_t qi[5];
#pragma unroll
    for (int k = 0; k < 5; k++) asm volatile("ld.global.nc.u32 %0, [%1];" : "=r"(qi[k]) : "l"(g_qidx + tid + 128 * k));
    if (tid >= 96) at<uint4>(sp, S_U + ((tid >> 4) & 1) * S_UPITCH + (tid & 15) * 16) = make_uint4(0, 0, 0, 0);
    bar_sync(barid, 128);
    mbar_wait(ubar, ch & 1);
    {
      const uint16_t* rt = reinterpret_cast<const uint16_t*>(sp + S_RT);
      uint32_t kv[5][3];
#pragma unroll
      for (int k = 0; k < 5; k++) { kv[k][0] = rt[qi[k] & 1023]; kv[k][1] = rt[(qi[k] >> 10) & 1023]; kv[k][2] = rt[qi[k] >> 20]; }
      const int pe = 16 + 16 * tid, po = pe - 8;
      const uint32_t pv = tid < 64 ? 0u : (uint32_t)rt[((pe & 255) >> 3) * 24 + 12 + (pe >> 8)] | ((uint32_t)rt[((po & 255) >> 3) * 24 + 12 + (po >> 8)] << 16);
      uint4 uu[4];
#pragma unroll
      for (int k = 0; k < 4; k++) uu[k] = at<uint4>(sp, S_U + ((tid + k + 1) & 1) * S_UPITCH + (16 + ((tid + k - 3) >> 1)) * 16);
#pragma unroll
      for (int k = 0; k < 5; k++) at<uint2>(sp, S_Q + (tid + 128 * k) * 8) = make_uint2(kv[k][1] | (kv[k][0] << 16), kv[k][2] | (kv[k][1] << 16));
      at<uint32_t>(sp, S_P + tid * 4) = pv;
      const uint32_t* uw = reinterpret_cast<const uint32_t*>(uu);
      float ps[24];
      ps[0] = 0.f;
#pragma unroll
      for (int k = 0; k < 23; k++) ps[k + 1] = ps[k] + ((k & 1) ? bf_hi(uw[2 + k / 2]) : bf_lo(uw[2 + k / 2]));
      uint8_t* vp = sp + S_V + (tid >> 3) * 288 + (tid & 1) * 144 + ((tid >> 1) & 3) * 4;
#pragma unroll
      for (int k = 0; k < 8; k++) at<uint32_t>(vp, k * 16) = pack_bf16(ps[k + 9] - ps[k], ps[k + 16] - ps[k + 9]);
    }
    fence_async_smem();
    bar_sync(barid, 128);
    uint32_t acc[32];
    float far[8];
    {
      float acc0[64];
      conv_group<0>(acc0, acc, far, reinterpret_cast<const uint32_t*>(sp + S_Q) + 16 + 16 * w + g - 2 * t4,
                    reinterpret_cast<const uint32_t*>(sp + S_P) + 64 + 16 * w + g - t4, sb + S_U, sb + S_V);
    }
    bar_sync(barid, 128);
    {
      const uint32_t ya = sb + S_Y + w * S_YPITCH + 32 * w + (lane & 7) * 32 + ((lane >> 3) & 1) * 16 + (lane >> 4) * 256;
#pragma unroll
      for (int j = 0; j < 8; j++)
        stsm4t(ya + j * 512, acc[4 * j], acc[4 * j + 1], acc[4 * j + 2], acc[4 * j + 3]);
      if (lane < 2 * w) at<uint4>(sp, S_Y + w * S_YPITCH + lane * 16) = make_uint4(0, 0, 0, 0);
#pragma unroll
      for (int i = 0; i < 4; i++) at<uint32_t>(sp, S_YF + (16 * w + g + 8 * (i & 1)) * 32 + (i >> 1) * 16 + t4 * 4) = pack_bf16(far[2 * ((i & 1) + (i >> 1) * 2)], far[2 * ((i & 1) + (i >> 1) * 2) + 1]);
    }
    bar_sync(barid, 128);
#pragma unroll 1
    for (int k = 0; k < 2; k++) {
      uint4 z[4];
#pragma unroll
      for (int s = 0; s < 4; s++) z[s] = at<uint4>(sp, S_Y + s * S_YPITCH + (tid + 128 * k) * 16);
      float f[8] = {bf_lo(z[0].x), bf_hi(z[0].x), bf_lo(z[0].y), bf_hi(z[0].y), bf_lo(z[0].z), bf_hi(z[0].z), bf_lo(z[0].w), bf_hi(z[0].w)};
#pragma unroll
      for (int s = 1; s < 4; s++) { acc_bf2(f[0], f[1], z[s].x); acc_bf2(f[2], f[3], z[s].y); acc_bf2(f[4], f[5], z[s].z); acc_bf2(f[6], f[7], z[s].w); }
      if (k) { const uint4 zf = at<uint4>(sp, S_YF + tid * 16); acc_bf2(f[0], f[1], zf.x); acc_bf2(f[2], f[3], zf.y); acc_bf2(f[4], f[5], zf.z); acc_bf2(f[6], f[7], zf.w); }
      g_yt[d * 256 + tid + 128 * k] = make_uint4(pack_bf16(f[0], f[1]), pack_bf16(f[2], f[3]), pack_bf16(f[4], f[5]), pack_bf16(f[6], f[7]));
    }
    fence_async_smem();
    bar_sync(barid, 128);
  }
  if (tid == 0) flag_add(&g_misc[32]);
}

__device__ __forceinline__ void load_unit(const CUtensorMap* tmP, uint32_t sm, int mi, int fj, int u) {
  const uint32_t bar = sm + OFF_BAR + 8 * (B_AFULL + u);
  mbar_expect_tx(bar, kBlk);
  asm volatile("cp.async.bulk.tensor.4d.shared::cluster.global.mbarrier::complete_tx::bytes [%0], [%1, {%3, %4, %5, %3}], [%2];"
               :: "r"(sm + u * kBlk), "l"(tmP), "r"(bar), "r"(0), "r"(u * 8 + fj), "r"(mi) : "memory");
}
__device__ __forceinline__ void reduce_units(const Params& p, const CUtensorMap* tmP, uint32_t sm, int mi, int fj, uint32_t tag, int u0, int barid) {
  const int tid = fresh_tid() & 127, w = tid >> 5, lane = tid & 31;
  uint4* out4 = reinterpret_cast<uint4*>(p.out) + (mi * 128 + fj * 16 + (tid >> 3)) * 72 + (tid & 7);
  const uint32_t sa = sm + OFF_SSM + (lane & 15) * 128 + (((2 * w + (lane >> 4)) ^ (lane & 7)) << 4);
  const uint32_t la = sm + OFF_SSM + (tid >> 3) * 128 + (((tid ^ (tid >> 3)) & 7) << 4);
  const uint32_t ya = sm + OFF_SSM + (w * 16 + (lane >> 4) * 8 + (lane & 7)) * 32 + ((lane >> 3) & 1) * 16;
  mbar_wait(sm + OFF_BAR + 8 * B_PAR, 0);
  mbar_wait(sm + OFF_BAR + 8 * B_UBAR, 0);
#pragma unroll 1
  for (int u = u0; u < 9; u += 3) {
    uint4 x[8], b, y;
    ldsm4t(ya + u * 2048, y.x, y.y, y.z, y.w);
    ldsm4(sa + u * 2048 + (OFF_RING + 2 * kBlk - OFF_SSM), b.x, b.y, b.z, b.w);
#pragma unroll 1
    for (int tries = 0; tries < 2000; tries++) {
      mbar_wait(sm + OFF_BAR + 8 * (B_AFULL + u), tries & 1);
      uint32_t bad = 0;
#pragma unroll
      for (int s = 0; s < 8; s++) { lds128(sm + u * kBlk + s * 2048 + tid * 16, x[s]); bad |= x[s].x ^ tag; x[s].x &= ~kTagMask; }
      uint32_t any;
      asm volatile("{\n.reg .pred p, q;\nsetp.ne.u32 p, %1, 0;\nbar.red.or.pred q, %2, 128, p;\nselp.u32 %0, 1, 0, q;\n}" : "=r"(any) : "r"(bad & kTagMask), "r"(barid) : "memory");
      if (!any) break;
      if (tid == 0) { __nanosleep(kRetry); fence_async_smem(); load_unit(tmP, sm, mi, fj, u); }
    }
    float f[8] = {bf_lo(x[0].x), bf_hi(x[0].x), bf_lo(x[0].y), bf_hi(x[0].y), bf_lo(x[0].z), bf_hi(x[0].z), bf_lo(x[0].w), bf_hi(x[0].w)};
#pragma unroll
    for (int s = 1; s < 8; s++) { acc_bf2(f[0], f[1], x[s].x); acc_bf2(f[2], f[3], x[s].y); acc_bf2(f[4], f[5], x[s].z); acc_bf2(f[6], f[7], x[s].w); }
    stsm4(sa + u * 2048, pack_bf16(fmaf(f[0], 0.5f, bf_lo(b.x) + bf_lo(y.x)), fmaf(f[1], 0.5f, bf_hi(b.x) + bf_hi(y.x))),
          pack_bf16(fmaf(f[2], 0.5f, bf_lo(b.y) + bf_lo(y.y)), fmaf(f[3], 0.5f, bf_hi(b.y) + bf_hi(y.y))),
          pack_bf16(fmaf(f[4], 0.5f, bf_lo(b.z) + bf_lo(y.z)), fmaf(f[5], 0.5f, bf_hi(b.z) + bf_hi(y.z))),
          pack_bf16(fmaf(f[6], 0.5f, bf_lo(b.w) + bf_lo(y.w)), fmaf(f[7], 0.5f, bf_hi(b.w) + bf_hi(y.w))));
    bar_sync(barid, 128);
    lds128(la + u * 2048, b);
    out4[u * 8] = b;
  }
}

template<bool N64> __device__ __forceinline__ void mma2(float (&acc)[2][64], uint32_t alo, uint32_t ahi, uint32_t moff, uint32_t blo, int scale) {
  if (N64) { wg_ss_n64(acc[0], desc2(alo, ahi), desc_sw128(blo), scale); wg_ss_n64(acc[1], desc2(alo + moff, ahi), desc_sw128(blo), scale); }
  else { wg_ss_n128(acc[0], desc2(alo, ahi), desc_sw128(blo), scale); wg_ss_n128(acc[1], desc2(alo + moff, ahi), desc_sw128(blo), scale); }
}

template<bool N64> __device__ __forceinline__ void mainloop(float (&acc)[2][64], uint32_t sm, uint32_t rempty, int t128, uint32_t slot0, bool wait_a,
                                                            int other_bar, bool rot, bool a64, uint32_t prog0) {
  const uint32_t bars = sm + OFF_BAR;
  const uint32_t alo0 = ((sm & 0x3FFFF) >> 4) | (1u << 16);
  const uint32_t ring = (((sm + OFF_RING) & 0x3FFFF) >> 4) | (512u << 16);
  const bool rel = t128 < 2, first = t128 == 0;
  const uint32_t ahi = a64 ? 0x80000020u : 0x40000040u, moff = a64 ? 256 : 512, k2 = a64 ? 512 : 4;
  if (wait_a) mbar_wait(bars + 8 * B_AFULL, 1);
  mbar_wait(bars + 8 * (B_FULL + (slot0 & 3)), (slot0 >> 2) & 1);
#pragma unroll 1
  for (int kb = 0; kb < 9; kb++) {
    const uint32_t slot = slot0 + (N64 ? kb >> 1 : kb), nslot = slot0 + (N64 ? (kb + 1) >> 1 : kb + 1);
    const uint32_t blo = ring + (slot & 3) * 1024 + (N64 ? (kb & 1) * 512 : 0);
    const uint32_t alo = alo0 + (!N64 && rot && kb < 8 ? (kb + 7) & 7 : kb) * 1024;
    pin(acc[0]); pin(acc[1]);
    wg_fence();
    mma2<N64>(acc, alo, ahi, moff, blo, kb);
    wg_commit();
    wg_wait<1>();
    mbar_arrive_remote_if(rempty + 8 * ((slot - 1) & 3), rel && kb > 0 && !(N64 && (kb & 1)) && slot <= 118);
    if (!N64) mbar_arrive_if(bars + 8 * B_X7FREE, rot && kb == 1 && first);
    sts_if(bars + 8 * B_PROG, prog0 + kb, first && kb > 0);
    asm volatile("{\n.reg .pred p;\nsetp.ne.u32 p, %1, 0;\n@p bar.arrive %0, 256;\n}" :: "r"(other_bar), "r"((uint32_t)(kb == 8 && other_bar)) : "memory");
    const uint32_t nb = bars + 8 * (B_FULL + (nslot & 3)), np = (nslot >> 2) & 1;
    asm volatile("mbarrier.test_wait.parity.shared::cta.b64 p_next_w, [%0], %1;" :: "r"(nb), "r"(np) : "memory");
    if (!N64)
      asm volatile("mbarrier.test_wait.parity.shared::cta.b64 p_next_a, [%0], %1;"
                   :: "r"(wait_a ? bars + 8 * (B_AFULL + kb + 1) : nb), "r"(wait_a ? 1u : np) : "memory");
    mma2<N64>(acc, alo + 2, ahi, moff, blo + 128, 1);
    mma2<N64>(acc, alo + k2, ahi, moff, blo + 256, 1);
    mma2<N64>(acc, alo + k2 + 2, ahi, moff, blo + 384, 1);
    wg_commit();
    pin(acc[0]); pin(acc[1]);
    uint32_t ok;
    if (N64) asm volatile("vote.sync.all.pred p_next_w, p_next_w, 0xffffffff;\nselp.u32 %0, 1, 0, p_next_w;" : "=r"(ok) :: "memory");
    else asm volatile("vote.sync.all.pred p_next_w, p_next_w, 0xffffffff;\nvote.sync.all.pred p_next_a, p_next_a, 0xffffffff;\n"
                      "and.pred p_next_w, p_next_w, p_next_a;\nselp.u32 %0, 1, 0, p_next_w;" : "=r"(ok) :: "memory");
    if (kb < 8 && !ok) {
      if (!N64 && wait_a) mbar_wait(bars + 8 * (B_AFULL + kb + 1), 1);
      mbar_wait(nb, np);
    }
  }
  wg_wait<0>();
  pin(acc[0]); pin(acc[1]);
  mbar_arrive_remote_if(rempty + 8 * ((slot0 + (N64 ? 4 : 8)) & 3), rel && other_bar);
  sts_if(bars + 8 * B_PROG, 126, first && !other_bar);
}

__global__ void __cluster_dims__(2, 1, 1) __launch_bounds__(512, 1)
fused_kernel(const __grid_constant__ CUtensorMap tmX, const __grid_constant__ CUtensorMap tmG, const __grid_constant__ CUtensorMap tmU,
             const __grid_constant__ CUtensorMap tmD2, const __grid_constant__ CUtensorMap tmD1, const __grid_constant__ CUtensorMap tmY,
             const __grid_constant__ CUtensorMap tmPs, const __grid_constant__ CUtensorMap tmX16,
             const Params p) {
  extern __shared__ __align__(1024) uint8_t smem_raw[];
  uint32_t sm = smem_u32(smem_raw);
  const int ch0 = blockIdx.x < kFfn ? blockIdx.x * 4 + (threadIdx.x >> 7) : 512 + (blockIdx.x - kFfn) * 16 + (threadIdx.x >> 7) * 4;
  ModePar mp = kgen_load(p, ch0);
  if (threadIdx.x >= 32) bar_arrive(9, 512);
  else {
    if (threadIdx.x < 9) mbar_init(sm + OFF_BAR + 8 * (B_AFULL + threadIdx.x), 1);
    fence_async_smem();
    bar_sync(9, 512);
  }
  if (threadIdx.x == 0 && blockIdx.x < kFfn) {
    mbar_expect_tx(sm + OFF_BAR + 8 * B_AFULL, 9 * kBlk);
    asm volatile("cp.async.bulk.tensor.3d.shared::cluster.global.mbarrier::complete_tx::bytes [%0], [%1, {%3, %4, %3}], [%2];"
                 :: "r"(sm), "l"(&tmX), "r"(sm + OFF_BAR + 8 * B_AFULL), "r"(0), "r"((blockIdx.x & 15) * 128) : "memory");
  } else if (threadIdx.x < 9) {
    mbar_arrive(sm + OFF_BAR + 8 * (B_AFULL + threadIdx.x));
  }
  asm volatile("mov.u32 %0, %0;" : "+r"(sm));
  sm = __shfl_sync(0xffffffffu, sm, 0);
  const uint32_t bars = sm + OFF_BAR;
  const int tid = threadIdx.x, lane = tid & 31, g = lane >> 2;
  const int warp = __shfl_sync(0xffffffffu, tid >> 5, 0), wg = warp >> 2;
  const int b = blockIdx.x, mi = b & 15, fj = b >> 4, rank = b & 1;
  const bool ffn = b < kFfn;
  const CUtensorMap* tmW = rank ? &tmU : &tmG;
  if (tid == 32) {
    for (int s = 0; s < kStages; s++) { mbar_init(bars + 8 * (B_FULL + s), 1); mbar_init(bars + 8 * (B_EMPTY + s), 2); }
    for (int s = 0; s < 7; s++) mbar_init(bars + 8 * (B_HREADY + s), 1);
    at<uint32_t>(smem_raw, OFF_BAR + 8 * B_PROG) = 0u;
    mbar_init(bars + 8 * B_X7FREE, 3);
    for (int s = 0; s < 5; s++) mbar_init(bars + 8 * (B_UBAR + s), 1);
    asm volatile("fence.mbarrier_init.release.cluster;" ::: "memory");
  } else if (tid == 64 && ffn) {
    tma2d_pf(tmW, fj * 576, (mi >> 1) * 64);
    if (mi < 2) tma2d_pf(tmW, fj * 576, 8 * 64);
    tma2d_pf(tmW, fj * 576 + 64, (mi >> 1) * 64);
    if (mi < 2) tma2d_pf(tmW, fj * 576 + 64, 8 * 64);
  }
  __syncwarp();
  if (wg == 0) bar_arrive(10, 512);
  float st[4][4];
#pragma unroll
  for (int i = 0; i < 16; i++) (&st[0][0])[i] = 0.f;
  const uint32_t xa0 = sm + (warp * 8 + (lane & 7)) * 128 + (((lane >> 3) ^ (lane & 7)) << 4), xa1 = xa0 ^ 64;
#pragma unroll 1
  for (int i = 0; i < (ffn ? 1 : 4); i++) {
    ModePar nx = mp;
    if (!ffn && i < 3) nx = kgen_load(p, ch0 + i + 1);
    kgen(mp, smem_raw + OFF_RING + wg * kBlk, ch0 + i, 3 + wg);
    mp = nx;
  }
  if (wg != 0) bar_sync(10, 512);
  cluster_arrive();
  if (wg == 3) {
    cluster_wait();
    if (lane == 0 && ffn) {
      const int s = warp & 3;
      mbar_expect_tx(bars + 8 * (B_FULL + s), kBlk);
      tma2d_mc(sm + OFF_RING + s * kBlk + rank * 8192, tmW, fj * 576, s * 64, bars + 8 * (B_FULL + s));
    }
    __syncwarp();
  }
  if (ffn) {
    uint32_t xv[9][8];
    mbar_wait(bars + 8 * B_AFULL, 0);
#pragma unroll
    for (int kb = 0; kb < 9; kb++) {
      ldsm4(xa0 + kb * kBlk, xv[kb][0], xv[kb][1], xv[kb][2], xv[kb][3]);
      ldsm4(xa1 + kb * kBlk, xv[kb][4], xv[kb][5], xv[kb][6], xv[kb][7]);
    }
#pragma unroll
    for (int kb = 0; kb < 9; kb++)
#pragma unroll
      for (int i = 0; i < 4; i++) hmma(st[i], xv[kb][2 * i], 0x3f803f80u, xv[kb][2 * i + 1], 0x3f803f80u, xv[kb][2 * i], xv[kb][2 * i + 1]);
#pragma unroll
    for (int i = 0; i < 4; i++) st[0][i] = (st[0][i] + st[1][i]) + (st[2][i] + st[3][i]);
    const float sumsq = __shfl_sync(0xffffffffu, (g & 1) ? st[0][1] : st[0][0], (lane & 28) | (g >> 1));
    const float se = __shfl_sync(0xffffffffu, st[0][2], g >> 1), so = __shfl_sync(0xffffffffu, st[0][3], g >> 1);
    const float mean = ((g & 1) ? so : se) * (1.f / kD);
    const float var = fmaxf(fmaf(-mean, mean, sumsq * (1.f / kD)), 0.f);
    const float rs = __frcp_rn(bf_round(__fsqrt_rn(bf_round(bf_round(var) + 1e-5f))));
    const float rh = bf_round(rs), mr = -bf_round(mean) * rs;
    const uint32_t nm2 = pack_bf16(mr, mr), rh2 = pack_bf16(rh, rh), rl2 = pack_bf16(rs - rh, rs - rh);
#pragma unroll
    for (int kb = 0; kb < 9; kb++) {
#pragma unroll
      for (int i = 0; i < 8; i++) xv[kb][i] = bf2_fma(xv[kb][i], rh2, bf2_fma(xv[kb][i], rl2, nm2));
      stsm4(xa0 + kb * kBlk, xv[kb][0], xv[kb][1], xv[kb][2], xv[kb][3]);
      stsm4(xa1 + kb * kBlk, xv[kb][4], xv[kb][5], xv[kb][6], xv[kb][7]);
    }
    fence_async_smem();
  }
  if (wg != 3) cluster_wait();

  if (!ffn || wg == 2) {
    reg_dec<120>();
    ROLE_LOCALS
    const bool ffn = b < kFfn;
    const unsigned epoch = read_epoch();
    bar_sync(15, 512);
    if (ffn) {
      const int w = warp & 3, t128 = tid & 127, rg = 4 * w + (lane >> 3);
      const uint32_t ua = sm + (8 * rg + (lane & 7)) * 128;
      const uint32_t us = sm + OFF_SSM + (lane & 7) * 256 + (((((rg & 1) << 3) | (rg >> 1)) ^ (lane & 7)) << 4);
#pragma unroll 3
      for (int i = 0; i < 9; i++) {
        const int cc = 9 * fj + i;
        uint32_t r0, r1, r2, r3;
        ldsm4(ua + (cc >> 3) * kBlk + (((cc ^ lane) & 7) << 4), r0, r1, r2, r3);
        stsm4t(us + i * 2048, r0, r1, r2, r3);
      }
      bar_sync(5, 128);
      if (tid == 256) mbar_arrive(bars + 8 * B_X7FREE);
      const int dl = t128 >> 4, sl = t128 & 15;
#pragma unroll 3
      for (int i = 0; i < 9; i++)
        g_ut[(72 * fj + 8 * i + dl) * 256 + (sl >> 3) * 128 + mi * 8 + (sl & 7)] = at<uint4>(smem_raw, OFF_SSM + i * 2048 + dl * 256 + ((sl ^ dl) << 4));
      fence_async_smem();
      bar_arrive(11, 160);
      bar_sync(5, 128);
    }
    uint8_t* sp = smem_raw + (ffn ? OFF_SSM : wg * 19456);
    ssm_role(sp, bars + 8 * (B_UBAR + wg), ffn ? 4 * b : 512 + (b - kFfn) * 16 + wg * 4, 3 + wg, epoch);
    if (fresh_cta() < kFfn) {
      ROLE_LOCALS
      if (tid == 256) {
        flag_wait(&g_misc[32], 144 * epoch);
        fence_async_all();
        mbar_expect_tx(bars + 8 * B_PAR, kD * 32);
        for (int i = 0; i < 3; i++) tma2d(sm + OFF_SSM + i * 6144, &tmY, mi * 128 + fj * 16, i * 192, bars + 8 * B_PAR);
      }
      if (tid == 256) prog_wait(bars + 8 * B_PROG, 126);
      bar_sync(5, 128);
      reduce_units(p, &tmPs, sm, mi, fj, epoch & 1 ? 1u : 0x10000u, 0, 5);
    }
    if (threadIdx.x == 256) g_launch[blockIdx.x * 32] = epoch;
  } else if (wg == 3) {
    reg_dec<40>();
    ROLE_LOCALS
    const int rank = b & 1;
    const CUtensorMap* tmW = rank ? &tmU : &tmG;
    bar_sync(15, 512);
    if (tid == 384) {
      int tile = 0, kb = kStages;
#pragma unroll 1
      for (int slot = kStages; slot < 13 * 9 + 5; slot++) {
        const int s = slot & (kStages - 1);
        mbar_wait(bars + 8 * (B_EMPTY + s), ((slot / kStages) & 1) ^ 1);
        const uint32_t dst = sm + OFF_RING + s * kBlk, fb = bars + 8 * (B_FULL + s);
        if (tile < 9) {
          mbar_expect_tx(fb, kBlk);
          tma2d_mc(dst + rank * 8192, tmW, fj * 576 + tile * 64, (tile == 8 && kb < 8 ? (kb + 7) & 7 : kb) * 64, fb);
        } else if (tile != 12) {
          mbar_expect_tx(fb, kBlk);
          tma5d_mc(dst + rank * 8192, &tmD2, (tile < 13 ? (tile - 9) * 128 : 448) + rank * 64, fj * 18 + kb * 2, fb);
        } else {
          if (kb < 4) {
            mbar_expect_tx(fb, kBlk);
            tma5d_mc(dst + rank * 8192, &tmD2, 384, fj * 18 + kb * 4 + rank * 2, fb);
          } else {
            mbar_expect_tx(fb, kBlk / 2);
            tma5d_mc(dst + rank * 4096, &tmD1, 384, fj * 18 + 16 + rank, fb);
          }
        }
        if (++kb == (tile == 12 ? 5 : 9)) {
          kb = 0; tile++;
          if (tile + 1 < 9) {
            tma2d_pf(tmW, fj * 576 + (tile + 1) * 64, (mi >> 1) * 64);
            if (mi < 2) tma2d_pf(tmW, fj * 576 + (tile + 1) * 64, 8 * 64);
          }
          const int nt = tile + 2;
          if (nt >= 9 && nt < 14) {
            const int c0 = (nt < 13 ? (nt - 9) * 128 : 448) + rank * 64;
            tma5d_pf(&tmD2, c0, fj * 18 + (mi >> 1) * 2);
            if (mi < 2) tma5d_pf(&tmD2, c0, fj * 18 + 16);
          }
          if (tile == 6) { tmap_pf(&tmD2); tmap_pf(&tmD1); }
          if (tile == 12) bulk_pf(p.u + (size_t)(mi * 128 + fj * 16) * kD, 16 * kD * 2);
        }
      }
    }
    if (warp == 14) {
      prog_wait(bars + 8 * B_PROG, 12);
#pragma unroll 1
      for (int i = 0; i < 64; i++) { g_h[(size_t)b * 9216 + 7168 + i * 32 + lane] = make_uint4(0, 0, 0, 0); __nanosleep(100); }
      __syncwarp();
      if (lane == 0) mbar_arrive(bars + 8 * B_X7FREE);
    }
    if (warp == 15) {
      bar_sync(11, 160);
      if (lane == 0) flag_add(&g_misc[0]);
      __syncwarp();
    }
    {
      if (tid == 416) {
        const unsigned epoch = read_epoch();
#pragma unroll 1
        for (int i = 0; i < 8; i++) mbar_wait(bars + 8 * (B_HREADY + i), 0);
        fence_async_all();
#pragma unroll 1
        for (int hb = 0; hb < 7; hb++) {
          prog_wait(bars + 8 * B_PROG, 74 + (hb * kHNum) / 3);
          mbar_expect_tx(bars + 8 * (B_AFULL + hb), kBlk);
          bulk_g2s(sm + hb * kBlk, g_h + ((size_t)b * 9 + hb) * 1024, kBlk, bars + 8 * (B_AFULL + hb));
        }
        tmap_pf(&tmPs); tmap_pf(&tmX16);
#pragma unroll 1
        for (int u = 0; u < 7; u++) {
          prog_wait(bars + 8 * B_PROG, min(118 + (u * kUNum) / 3, 126));
          if (u == 4) {
            prog_wait(bars + 8 * B_PROG, 124);
            mbar_expect_tx(bars + 8 * B_UBAR, 9 * 2048);
            asm volatile("cp.async.bulk.tensor.3d.shared::cluster.global.mbarrier::complete_tx::bytes [%0], [%1, {%3, %4, %3}], [%2];"
                         :: "r"(sm + OFF_RING + 2 * kBlk), "l"(&tmX16), "r"(bars + 8 * B_UBAR), "r"(0), "r"(mi * 128 + fj * 16) : "memory");
          }
          load_unit(&tmPs, sm, mi, fj, u);
        }
        prog_wait(bars + 8 * B_PROG, 127);
        {
          const unsigned target = 8 * epoch;
#pragma unroll 1
          for (int n = 0; n < 20000; n++) {
            unsigned v;
            asm volatile("ld.relaxed.gpu.global.u32 %0, [%1];" : "=r"(v) : "l"(&g_hint[mi * 32]) : "memory");
            if ((int)(v - target) >= 0) break;
            __nanosleep(20);
          }
        }
        __nanosleep(kLate);
        load_unit(&tmPs, sm, mi, fj, 7); load_unit(&tmPs, sm, mi, fj, 8);
      }
    }
  } else {
    reg_inc<176>();
    ROLE_LOCALS
    const int w = warp & 3, t128 = tid & 127, g = lane >> 2, t4 = lane & 3;
    const uint32_t rempty = mapa(bars + 8 * B_EMPTY, t128 & 1);
    const uint32_t tag = read_epoch() & 1 ? 1u : 0x10000u;
    float acc[2][64];
    asm volatile(".reg .pred p_next_w, p_next_a;");
    bar_sync(15, 512);
#pragma unroll 1
    for (int tile = wg; tile < 14; tile += 2) {
      if (tile > 0) bar_sync(1 + wg, 256);
      if (tile != 12) mainloop<false>(acc, sm, rempty, t128, tile < 13 ? tile * 9 : 113, tile == 9 || tile == 10, tile < 13 ? 1 + (wg ^ 1) : 0, tile == 8,
                                      tile >= 9, tile * 9);
      else mainloop<true>(acc, sm, rempty, t128, 108, false, 2, false, true, 108);
      if (tile < 9) {
        uint4* hb = g_h + ((size_t)b * 9 + tile) * 1024;
        if (tile >= 7) mbar_wait(bars + 8 * B_X7FREE, 0);
#pragma unroll
        for (int mh = 0; mh < 2; mh++)
#pragma unroll
          for (int hh = 0; hh < 2; hh++)
#pragma unroll
            for (int jh = 0; jh < 2; jh++) {
              uint32_t v[4];
#pragma unroll
              for (int jl = 0; jl < 4; jl++) {
                const int i = 4 * (4 * jh + jl) + 2 * hh;
                v[jl] = gelu_mul2(acc[mh][i], acc[mh][i + 1], acc[mh][32 + i], acc[mh][33 + i]);
              }
              const int idx = jh * 512 + (64 * mh + 16 * w + 8 * hh + g) * 4 + (t4 ^ (g >> 1));
              if (tile < 7) hb[idx] = make_uint4(v[0] & ~kTagMask, v[1], v[2], v[3]);
              else at<uint4>(smem_raw, tile * kBlk + idx * 16) = make_uint4(v[0], v[1], v[2], v[3]);
            }
        if (tile >= 7) fence_async_smem();
        bar_sync(7 + wg, 128);
        if (t128 == 0) mbar_arrive(bars + 8 * (tile < 7 ? B_HREADY + tile : B_AFULL + tile));
      } else {
        const bool big = tile != 12;
        uint4* pb = g_h + (size_t)b * 9216 + (tile < 13 ? 2 * (tile - 9) : 7) * 1024 + w * 128 + lane;
#pragma unroll
        for (int qm = 0; qm < 16; qm++) {
            const int mh = (qm >> 2) & 1, q = (qm & 3) + (qm >> 3) * 4;
            if (q < 4 || big) {
              st_part(pb + (q >> 2) * 1024 + mh * 512 + (q & 3) * 32,
                  make_uint4((pack_bf16(acc[mh][8 * q], acc[mh][8 * q + 1]) & ~kTagMask) | tag, pack_bf16(acc[mh][8 * q + 2], acc[mh][8 * q + 3]),
                             pack_bf16(acc[mh][8 * q + 4], acc[mh][8 * q + 5]), pack_bf16(acc[mh][8 * q + 6], acc[mh][8 * q + 7])));
              if (tile < 11) __nanosleep(kPace);
            }
        }
      }
    }
    {
    ROLE_LOCALS
    const int t128 = tid & 127;
    if (t128 == 0 && wg == 0) prog_wait(bars + 8 * B_PROG, 126);
    bar_sync(7 + wg, 128);
    if (t128 == 0 && wg == 1) {
      asm volatile("red.relaxed.gpu.global.add.u32 [%0], 1;" :: "l"(&g_hint[mi * 32]) : "memory");
      sts_if(bars + 8 * B_PROG, 127, true);
    }
    reduce_units(p, &tmPs, sm, mi, fj, tag, 1 + wg, 7 + wg);
    }
  }
}

__global__ void fb_ln(const Params p) {
  const int row = blockIdx.x * 8 + (threadIdx.x >> 5), lane = threadIdx.x & 31;
  float s1 = 0.f, s2 = 0.f;
  for (int c = lane; c < kD; c += 32) s1 += __bfloat162float(p.u[row * kD + c]);
  for (int o = 16; o > 0; o >>= 1) s1 += __shfl_xor_sync(0xffffffffu, s1, o);
  s1 *= 1.f / kD;
  for (int c = lane; c < kD; c += 32) { const float a = __bfloat162float(p.u[row * kD + c]) - s1; s2 += a * a; }
  for (int o = 16; o > 0; o >>= 1) s2 += __shfl_xor_sync(0xffffffffu, s2, o);
  const float sd = bf_round(sqrtf(bf_round(bf_round(s2 * (1.f / kD)) + 1e-5f)));
  __nv_bfloat16* xn = reinterpret_cast<__nv_bfloat16*>(g_yt);
  for (int c = lane; c < kD; c += 32) xn[row * kD + c] = __float2bfloat16(bf_round(__bfloat162float(p.u[row * kD + c]) - bf_round(s1)) / sd);
}
__global__ void fb_conv(const Params p) {
  __shared__ float K[kL], U[kL];
  const int d = blockIdx.x;
  const __nv_bfloat16* xn = reinterpret_cast<const __nv_bfloat16*>(g_yt);
  const float dt = bf_round(expf(__bfloat162float(p.logdt[d])));
  for (int j = threadIdx.x; j < kL; j += blockDim.x) {
    const float pos = bf_round((float)j);
    float acc = 0.f;
    for (int n = 0; n < kN; n++) {
      float zr, zi;
      cexp_at(-bf_round(expf(__bfloat162float(p.logA[d * kN + n]))) * dt * 1.4426950408889634f, __bfloat162float(p.Aim[d * kN + n]) * dt, pos, zr, zi);
      acc += __bfloat162float(p.Cre[d * kN + n]) * dt * zr - __bfloat162float(p.Cim[d * kN + n]) * dt * zi;
    }
    K[j] = 2.f * acc + (j == 0 ? __bfloat162float(p.Dskip[d]) : 0.f);
    U[j] = __bfloat162float(xn[j * kD + d]);
  }
  __syncthreads();
  for (int l = threadIdx.x; l < kL; l += blockDim.x) {
    float acc = 0.f;
    for (int j = 0; j <= l; j++) acc += K[j] * U[l - j];
    reinterpret_cast<__nv_bfloat16*>(g_ut)[l * kD + d] = __float2bfloat16(acc);
  }
}
__global__ void fb_h(const __nv_bfloat16* wg, const __nv_bfloat16* wu) {
  __shared__ float X[kD];
  const int f = blockIdx.x * 256 + threadIdx.x, row = blockIdx.y;
  for (int c = threadIdx.x; c < kD; c += 256) X[c] = __bfloat162float(reinterpret_cast<const __nv_bfloat16*>(g_yt)[row * kD + c]);
  __syncthreads();
  float g = 0.f, u = 0.f;
  for (int c = 0; c < kD; c++) { g += X[c] * __bfloat162float(wg[c * kF + f]); u += X[c] * __bfloat162float(wu[c * kF + f]); }
  reinterpret_cast<__nv_bfloat16*>(g_h)[(size_t)row * kF + f] = __float2bfloat16(0.5f * g * (1.f + tanhf(0.7978845608f * (g + 0.044715f * g * g * g))) * u);
}
__global__ void fb_out(const Params p) {
  const int c = blockIdx.x * 192 + threadIdx.x, row = blockIdx.y;
  const __nv_bfloat16* h = reinterpret_cast<const __nv_bfloat16*>(g_h) + (size_t)row * kF;
  float acc = 0.f;
  for (int f = 0; f < kF; f++) acc += __bfloat162float(h[f]) * __bfloat162float(p.wdown[f * kD + c]);
  p.out[row * kD + c] = __float2bfloat16(acc + __bfloat162float(p.u[row * kD + c]) + __bfloat162float(reinterpret_cast<const __nv_bfloat16*>(g_ut)[row * kD + c]));
}

typedef CUresult (*EncodeFn)(CUtensorMap*, CUtensorMapDataType, cuuint32_t, void*, const cuuint64_t*, const cuuint64_t*, const cuuint32_t*,
                             const cuuint32_t*, CUtensorMapInterleave, CUtensorMapSwizzle, CUtensorMapL2promotion, CUtensorMapFloatOOBfill);

int encode(EncodeFn fn, CUtensorMap* tm, void* base, int rank, const cuuint64_t* dims, const cuuint64_t* strides, const cuuint32_t* box,
           CUtensorMapSwizzle swz = CU_TENSOR_MAP_SWIZZLE_128B, CUtensorMapDataType dt = CU_TENSOR_MAP_DATA_TYPE_BFLOAT16) {
  cuuint32_t es[5] = {1, 1, 1, 1, 1};
  if (!fn) return -1;
  return (int)fn(tm, dt, rank, base, dims, strides, box, es, CU_TENSOR_MAP_INTERLEAVE_NONE,
                 swz, CU_TENSOR_MAP_L2_PROMOTION_L2_128B, CU_TENSOR_MAP_FLOAT_OOB_FILL_NONE);
}

}

extern "C" void kernel_launch(void* const* d_in, const int* in_sizes, int n_in, void* d_out, int out_size) {
  (void)in_sizes; (void)n_in; (void)out_size;
  static CUtensorMap tmX, tmG, tmU, tmD2, tmD1, tmY, tmPs, tmX16;
  static bool resident = true;
  static const void* cached[4] = {nullptr, nullptr, nullptr, nullptr};
  if (cached[0] != d_in[8] || cached[1] != d_in[9] || cached[2] != d_in[10] || cached[3] != d_in[0]) {
    void* fnp = nullptr;
    cudaDriverEntryPointQueryResult qr;
    cudaGetDriverEntryPoint("cuTensorMapEncodeTiled", &fnp, cudaEnableDefault, &qr);
    EncodeFn fn = (EncodeFn)fnp;
    { cuuint64_t d3[3] = {64, kL, 9}, s3[2] = {kD * 2, 128}; cuuint32_t b3[3] = {64, 16, 9}; encode(fn, &tmX16, d_in[0], 3, d3, s3, b3);
      b3[1] = 128; encode(fn, &tmX, d_in[0], 3, d3, s3, b3); }
    { cuuint64_t dims[2] = {kF, kD}, st[1] = {kF * 2}; cuuint32_t box[2] = {64, 64};
      encode(fn, &tmG, d_in[8], 2, dims, st, box); encode(fn, &tmU, d_in[9], 2, dims, st, box); }
    { cuuint64_t dims[5] = {kD, 2, 4, 4, kF / 32}, st[4] = {kD * 2, kD * 2 * 8, kD * 2 * 2, kD * 2 * 32};
      cuuint32_t box2[5] = {64, 2, 4, 4, 2}, box1[5] = {64, 2, 4, 4, 1};
      encode(fn, &tmD2, d_in[10], 5, dims, st, box2); encode(fn, &tmD1, d_in[10], 5, dims, st, box1); }
    { void* yt = nullptr; cudaGetSymbolAddress(&yt, g_yt);
      cuuint64_t dims[2] = {kL, kD}, st[1] = {kL * 2}; cuuint32_t box[2] = {16, 192};
      encode(fn, &tmY, yt, 2, dims, st, box, CU_TENSOR_MAP_SWIZZLE_NONE); }
    { void* h = nullptr; cudaGetSymbolAddress(&h, g_h);
      cuuint64_t dims[4] = {256, 72, 16, 8}, st[3] = {2048, 147456, 16 * 147456}; cuuint32_t box[4] = {256, 1, 1, 8};
      encode(fn, &tmPs, h, 4, dims, st, box, CU_TENSOR_MAP_SWIZZLE_NONE, CU_TENSOR_MAP_DATA_TYPE_UINT64); }
    cudaFuncSetAttribute(fused_kernel, cudaFuncAttributeMaxDynamicSharedMemorySize, SMEM_TOTAL);
    { cudaLaunchConfig_t cfg = {}; cfg.gridDim = dim3(kCtas); cfg.blockDim = dim3(512); cfg.dynamicSmemBytes = SMEM_TOTAL;
      cudaLaunchAttribute at; at.id = cudaLaunchAttributeClusterDimension; at.val.clusterDim.x = 2; at.val.clusterDim.y = at.val.clusterDim.z = 1;
      cfg.attrs = &at; cfg.numAttrs = 1;
      int n = 0;
      resident = fn && cudaOccupancyMaxActiveClusters(&n, fused_kernel, &cfg) == cudaSuccess && n >= kCtas / 2;
      (void)cudaGetLastError(); }
    cached[0] = d_in[8]; cached[1] = d_in[9]; cached[2] = d_in[10]; cached[3] = d_in[0];
  }
  Params p;
  p.u = (const __nv_bfloat16*)d_in[0]; p.logA = (const __nv_bfloat16*)d_in[1]; p.Aim = (const __nv_bfloat16*)d_in[2];
  p.Cre = (const __nv_bfloat16*)d_in[3]; p.Cim = (const __nv_bfloat16*)d_in[4]; p.logdt = (const __nv_bfloat16*)d_in[5];
  p.Dskip = (const __nv_bfloat16*)d_in[6]; p.wdown = (const __nv_bfloat16*)d_in[10]; p.out = (__nv_bfloat16*)d_out;
  if (!resident) {
    fb_ln<<<kL / 8, 256>>>(p);
    fb_conv<<<kD, 256>>>(p);
    fb_h<<<dim3(kF / 256, kL), 256>>>((const __nv_bfloat16*)d_in[8], (const __nv_bfloat16*)d_in[9]);
    fb_out<<<dim3(3, kL), 192>>>(p);
    return;
  }
  fused_kernel<<<kCtas, 512, SMEM_TOTAL>>>(tmX, tmG, tmU, tmD2, tmD1, tmY, tmPs, tmX16, p);
}
```
